```python
import torch

def _softmax(x, axis=-1):
    return torch.softmax(x, dim=axis)
def _gelu(x):
    return torch.nn.functional.gelu(x, approximate="tanh")
def _silu(x):
    return torch.nn.functional.silu(x)
def _sigmoid(x):
    return torch.sigmoid(x)
def _layernorm(x, axis=-1, eps=1e-5):
    m = x.mean(dim=axis, keepdim=True)
    v = x.var(dim=axis, keepdim=True, unbiased=False)
    return (x - m) / torch.sqrt(v + eps)
def _scatter_add(tgt, idx, src, axis=0):
    return tgt.clone().index_add_(axis, idx, src)
def _segment_sum(src, seg, n):
    out = torch.zeros((n,) + src.shape[1:], dtype=src.dtype)
    return out.index_add_(0, seg, src)
def _pad(x, pw):
    flat = tuple(v for pair in reversed(pw) for v in pair)
    return torch.nn.functional.pad(x, flat)

kernel_name = 'concat_heads__mha_block_cached__mha_block_cached__near_ridge'

def setup_inputs():

    _w = (lambda a: (lambda t: t.to(torch.bfloat16) if t.is_floating_point() else t)(torch.as_tensor(a)))
    def _A_setup():
        B, Sq, D = 8, 192, 1024
        H, Sk, Dh = 32, 1024, 128
        return {
            "x": _w((lambda *s: torch.randn(*s, dtype=torch.bfloat16) * 0.8)(B, Sq, D)),
            "k_cache": _w((lambda *s: torch.randn(*s, dtype=torch.bfloat16) * 0.8)(B, H, Sk, Dh)),
            "v_cache": _w((lambda *s: torch.randn(*s, dtype=torch.bfloat16) * 0.05)(B, H, Sk, Dh)),
            "wq": _w((lambda *s: torch.randn(*s, dtype=torch.bfloat16) * 0.8)(D, H * Dh) * (D ** -0.5)),
            "wo": _w((lambda *s: torch.randn(*s, dtype=torch.bfloat16) * 0.05)(H * Dh, D) * ((H * Dh) ** -0.5)),
        }
    _A_in = _A_setup()

    def _B_setup():
        B, Sq, D = 8, 192, 1024
        H, Sk, Dh = 32, 1024, 128
        return {
            "x": _w((lambda *s: torch.randn(*s, dtype=torch.bfloat16) * 0.8)(B, Sq, D)),
            "k_cache": _w((lambda *s: torch.randn(*s, dtype=torch.bfloat16) * 0.8)(B, H, Sk, Dh)),
            "v_cache": _w((lambda *s: torch.randn(*s, dtype=torch.bfloat16) * 0.05)(B, H, Sk, Dh)),
            "wq": _w((lambda *s: torch.randn(*s, dtype=torch.bfloat16) * 0.8)(D, H * Dh) * (D ** -0.5)),
            "wo": _w((lambda *s: torch.randn(*s, dtype=torch.bfloat16) * 0.05)(H * Dh, D) * ((H * Dh) ** -0.5)),
        }
    _B_in = _B_setup()

    return {
        "A_x": _A_in["x"],
        "A_k_cache": _A_in["k_cache"],
        "A_v_cache": _A_in["v_cache"],
        "A_wq": _A_in["wq"],
        "A_wo": _A_in["wo"],
        "B_x": _B_in["x"],
        "B_k_cache": _B_in["k_cache"],
        "B_v_cache": _B_in["v_cache"],
        "B_wq": _B_in["wq"],
        "B_wo": _B_in["wo"],
    }

def reference(A_x, A_k_cache, A_v_cache, A_wq, A_wo, B_x, B_k_cache, B_v_cache, B_wq, B_wo):
    def _A_ref(x, k_cache, v_cache, wq, wo):
        B, Sq, D = x.shape
        H, Dh = 32, 128
        q = (lambda x, *d: x.permute(*d))((x @ wq).reshape(B, Sq, H, Dh), 0, 2, 1, 3)
        scores = torch.einsum("bhqd,bhkd->bhqk", q, k_cache) * (Dh ** -0.5)
        p = _softmax(scores, axis=-1)
        o = torch.einsum("bhqk,bhkd->bhqd", p, v_cache)
        return (lambda x, *d: x.permute(*d))(o, 0, 2, 1, 3).reshape(B, Sq, H * Dh) @ wo

    def _B_ref(x, k_cache, v_cache, wq, wo):
        B, Sq, D = x.shape
        H, Dh = 32, 128
        q = (lambda x, *d: x.permute(*d))((x @ wq).reshape(B, Sq, H, Dh), 0, 2, 1, 3)
        scores = torch.einsum("bhqd,bhkd->bhqk", q, k_cache) * (Dh ** -0.5)
        p = _softmax(scores, axis=-1)
        o = torch.einsum("bhqk,bhkd->bhqd", p, v_cache)
        return (lambda x, *d: x.permute(*d))(o, 0, 2, 1, 3).reshape(B, Sq, H * Dh) @ wo

    a = _A_ref(A_x, A_k_cache, A_v_cache, A_wq, A_wo)
    b = _B_ref(B_x, B_k_cache, B_v_cache, B_wq, B_wo)
    return torch.concatenate([a, b], axis=-1)
```

```cpp
#include <cuda_runtime.h>
#include <cuda_bf16.h>
#include <cuda.h>
#include <stdint.h>

namespace {

constexpr int NB = 8, SQ = 192, DM = 1024, NH = 32, SK = 1024, DH = 128;
constexpr int NCTA = 132;
constexpr int MAXOPS = 10;
constexpr int NTHREADS = 512;

constexpr uint32_t A_SLOT = 24576;
constexpr uint32_t B_SLOT = 32768;
constexpr uint32_t OFF_A = 0;
constexpr uint32_t OFF_B = 4 * A_SLOT;
constexpr uint32_t OFF_BAR = OFF_B + 4 * B_SLOT;
constexpr uint32_t BAR_FULL = OFF_BAR;
constexpr uint32_t BAR_EMPTY = OFF_BAR + 32;
constexpr uint32_t BAR_QFREE = OFF_BAR + 64;
constexpr uint32_t BAR_STAGED = OFF_BAR + 80;
constexpr uint32_t BAR_QREADY = OFF_BAR + 104;
constexpr uint32_t BAR_QLOAD = OFF_BAR + 128;
constexpr uint32_t SMEM_BYTES = OFF_BAR + 256;

struct Params {
    CUtensorMap x[2], wq[2], k[2], v[2], wo[2], out;
    int never;
    uint16_t ops[NCTA][MAXOPS];
};

enum : uint32_t { OP_END = 0, OP_Q = 1, OP_AT = 2, OP_OT = 3 };
enum : uint32_t { Q_TWO = 1u << 11, Q_ST0 = 1u << 12, Q_ST1 = 1u << 13,
                  AT_STASH = 1u << 11, AT_BUF1 = 1u << 12, AT_LAST = 1u << 13 };
__host__ __device__ constexpr uint32_t op_k1(uint32_t op) { return (op >> 11) * 4; }
__host__ __device__ constexpr bool op_takeover(uint32_t op) { return (op >> 8) & 1; }
__host__ __device__ constexpr uint32_t op_tile(uint32_t op) { return ((op >> 2) & 15) * 4 + ((op >> 6) & 3); }
__host__ __device__ constexpr uint32_t op_type(uint32_t op) { return op & 3; }
__host__ __device__ constexpr uint32_t op_g(uint32_t op) { return (op >> 2) & 15; }
__host__ __device__ constexpr uint32_t op_h(uint32_t op) { return (op >> 6) & 31; }
__host__ __device__ constexpr uint32_t op_head(uint32_t op) { return op_g(op) * NH + op_h(op); }

__device__ uint4 g_o[2 * NB * NH * 2 * (A_SLOT / 16)];
__device__ unsigned g_flag[2 * NB * NH];
__device__ unsigned g_qflag[2 * NB * NH * 4];
__device__ float4 g_park[64 * 12 * 16 * 32];
__device__ unsigned g_pflag[64 * 4];
__device__ unsigned g_epoch[NCTA];
#define TR(t, i)

#define SCHED 1
#define CTA_N(g, j) ((g) * 8 + 2 * (j))
#define CTA_M(g, j) ((g) * 8 + 2 * (j) + 1)
#define TRACE_CTA 4
#define NPF 0
#define PF0 2
#define SM_CH 1
#define SM_LAG 2
#define FENCE_KIND 3
#define SCHED_FENCE(x) asm volatile("{\n.reg .pred p;\nsetp.ne.s32 p, %0, 0;\n@p exit;\n}" ::"r"(x))
#define S0MODE 2
#define WQPF 0
#define WQS 4
#define WQD 2
#define TMPF 1
#define PFS 6
#define PFD 3
#define PFALL 0
#define KPF 0
#define STAG 800
#define K1N 56
#define K1E 36
#define JUNC 1
#define LATEF 1
#define RESC 1
__device__ __forceinline__ uint32_t smem_u32(const void* p) { return (uint32_t)__cvta_generic_to_shared(p); }
__device__ __forceinline__ void mbar_init(uint32_t bar, uint32_t cnt) {
    asm volatile("mbarrier.init.shared::cta.b64 [%0], %1;" ::"r"(bar), "r"(cnt) : "memory");
}
__device__ __forceinline__ void mbar_expect_tx(uint32_t bar, uint32_t bytes) {
    asm volatile("mbarrier.arrive.expect_tx.shared::cta.b64 _, [%0], %1;" ::"r"(bar), "r"(bytes) : "memory");
}
__device__ __forceinline__ void mbar_arrive(uint32_t bar) {
    asm volatile("mbarrier.arrive.shared::cta.b64 _, [%0];" ::"r"(bar) : "memory");
}
__device__ __forceinline__ void mbar_wait(uint32_t bar, uint32_t parity) {
    asm volatile(
        "{\n.reg .pred p;\n.reg .u32 n;\nmov.u32 n, 0;\n"
        "LAB_WAIT:\n"
        "mbarrier.try_wait.parity.shared::cta.b64 p, [%0], %1;\n"
        "@p bra LAB_DONE;\n"
        "add.u32 n, n, 1;\nsetp.lt.u32 p, n, 0x200000;\n@p bra LAB_WAIT;\ntrap;\n"
        "LAB_DONE:\n}" ::"r"(bar), "r"(parity) : "memory");
}
__device__ __forceinline__ void mbar_wait_sleep(uint32_t bar, uint32_t parity) {
    asm volatile(
        "{\n.reg .pred p;\n.reg .u32 n;\nmov.u32 n, 0;\n"
        "LAB_WAIT:\n"
        "mbarrier.try_wait.parity.shared::cta.b64 p, [%0], %1, 20000;\n"
        "@p bra LAB_DONE;\n"
        "add.u32 n, n, 1;\nsetp.lt.u32 p, n, 0x10000;\n@p bra LAB_WAIT;\ntrap;\n"
        "LAB_DONE:\n}" ::"r"(bar), "r"(parity) : "memory");
}
__device__ __forceinline__ void flag_wait(const unsigned* p, unsigned target) {
    asm volatile(
        "{\n.reg .pred p;\n.reg .u32 n, v;\n.reg .s32 d;\nmov.u32 n, 0;\n"
        "LAB_WAIT:\n"
        "ld.acquire.gpu.global.u32 v, [%0];\n"
        "sub.s32 d, v, %1;\nsetp.ge.s32 p, d, 0;\n"
        "@p bra LAB_DONE;\n"
        "nanosleep.u32 64;\n"
        "add.u32 n, n, 1;\nsetp.lt.u32 p, n, 0x400000;\n@p bra LAB_WAIT;\ntrap;\n"
        "LAB_DONE:\n}" ::"l"(p), "r"(target) : "memory");
}
__device__ __forceinline__ void tma_2d(uint32_t dst, const CUtensorMap* m, int c0, int c1, uint32_t bar) {
    asm volatile("cp.async.bulk.tensor.2d.shared::cluster.global.mbarrier::complete_tx::bytes [%0], [%1, {%3, %4}], [%2];"
                 ::"r"(dst), "l"(m), "r"(bar), "r"(c0), "r"(c1) : "memory");
}
__device__ __forceinline__ void tma_3d(uint32_t dst, const CUtensorMap* m, int c0, int c1, int c2, uint32_t bar) {
    asm volatile("cp.async.bulk.tensor.3d.shared::cluster.global.mbarrier::complete_tx::bytes [%0], [%1, {%3, %4, %5}], [%2];"
                 ::"r"(dst), "l"(m), "r"(bar), "r"(c0), "r"(c1), "r"(c2) : "memory");
}
__device__ __forceinline__ void tma_3d_hint(uint32_t dst, const CUtensorMap* m, int c0, int c1, int c2, uint32_t bar, uint64_t pol) {
    asm volatile("cp.async.bulk.tensor.3d.shared::cluster.global.mbarrier::complete_tx::bytes.L2::cache_hint [%0], [%1, {%3, %4, %5}], [%2], %6;"
                 ::"r"(dst), "l"(m), "r"(bar), "r"(c0), "r"(c1), "r"(c2), "l"(pol) : "memory");
}
__device__ __forceinline__ void tma_2d_hint(uint32_t dst, const CUtensorMap* m, int c0, int c1, uint32_t bar, uint64_t pol) {
    asm volatile("cp.async.bulk.tensor.2d.shared::cluster.global.mbarrier::complete_tx::bytes.L2::cache_hint [%0], [%1, {%3, %4}], [%2], %5;"
                 ::"r"(dst), "l"(m), "r"(bar), "r"(c0), "r"(c1), "l"(pol) : "memory");
}
__device__ __forceinline__ void bulk_load_hint(uint32_t dst, const void* src, uint32_t bytes, uint32_t bar, uint64_t pol) {
    asm volatile("cp.async.bulk.shared::cluster.global.mbarrier::complete_tx::bytes.L2::cache_hint [%0], [%1], %2, [%3], %4;"
                 ::"r"(dst), "l"(src), "r"(bytes), "r"(bar), "l"(pol) : "memory");
}
__device__ __forceinline__ void bulk_load(uint32_t dst, const void* src, uint32_t bytes, uint32_t bar) {
    asm volatile("cp.async.bulk.shared::cluster.global.mbarrier::complete_tx::bytes [%0], [%1], %2, [%3];"
                 ::"r"(dst), "l"(src), "r"(bytes), "r"(bar) : "memory");
}
__device__ __forceinline__ void bulk_store(void* dst, uint32_t src, uint32_t bytes) {
    asm volatile("cp.async.bulk.global.shared::cta.bulk_group [%0], [%1], %2;" ::"l"(dst), "r"(src), "r"(bytes) : "memory");
}
__device__ __forceinline__ void tma_store_2d(const CUtensorMap* m, uint32_t src, int c0, int c1) {
    asm volatile("cp.async.bulk.tensor.2d.global.shared::cta.bulk_group [%0, {%2, %3}], [%1];"
                 ::"l"(m), "r"(src), "r"(c0), "r"(c1) : "memory");
}
__device__ __forceinline__ void tma_prefetch_3d(const CUtensorMap* m, int c0, int c1, int c2) {
    asm volatile("cp.async.bulk.prefetch.tensor.3d.L2.global [%0, {%1, %2, %3}];" ::"l"(m), "r"(c0), "r"(c1), "r"(c2) : "memory");
}
__device__ __forceinline__ void tma_prefetch_3d_hint(const CUtensorMap* m, int c0, int c1, int c2, uint64_t pol) {
    asm volatile("cp.async.bulk.prefetch.tensor.3d.L2.global.L2::cache_hint [%0, {%1, %2, %3}], %4;" ::"l"(m), "r"(c0), "r"(c1), "r"(c2), "l"(pol) : "memory");
}
__device__ __forceinline__ bool elect_one() {
    uint32_t r;
    asm volatile("{\n.reg .pred p;\nelect.sync _|p, 0xffffffff;\nselp.b32 %0, 1, 0, p;\n}" : "=r"(r));
    return r;
}
__device__ __forceinline__ void wg_fence() { asm volatile("wgmma.fence.sync.aligned;" ::: "memory"); }
__device__ __forceinline__ void wg_commit() { asm volatile("wgmma.commit_group.sync.aligned;" ::: "memory"); }
template <int N> __device__ __forceinline__ void wg_wait() { asm volatile("wgmma.wait_group.sync.aligned %0;" ::"n"(N) : "memory"); }
__device__ __forceinline__ void fence_async_smem() { asm volatile("fence.proxy.async.shared::cta;" ::: "memory"); }
__device__ __forceinline__ void bar_sync(int id) { asm volatile("bar.sync %0, 256;" ::"r"(id) : "memory"); }
__device__ __forceinline__ void bar_arrive(int id) { asm volatile("bar.arrive %0, 256;" ::"r"(id) : "memory"); }
__device__ __forceinline__ float ex2(float x) { float y; asm("ex2.approx.ftz.f32 %0, %1;" : "=f"(y) : "f"(x)); return y; }
__device__ __forceinline__ uint32_t pack_bf16(float lo, float hi) {
    uint32_t r; asm("cvt.rn.bf16x2.f32 %0, %1, %2;" : "=r"(r) : "f"(hi), "f"(lo)); return r;
}
__device__ __forceinline__ void stsm4(uint32_t addr, uint32_t a, uint32_t b, uint32_t c, uint32_t d) {
    asm volatile("stmatrix.sync.aligned.m8n8.x4.shared.b16 [%0], {%1, %2, %3, %4};" ::"r"(addr), "r"(a), "r"(b), "r"(c), "r"(d) : "memory");
}
template <int N> __device__ __forceinline__ void reg_fence(float (&d)[N]) {
#pragma unroll
    for (int i = 0; i < N; i++) asm volatile("" : "+f"(d[i])::"memory");
}

__device__ __forceinline__ uint64_t mk_desc(uint32_t addr, uint32_t lbo) {
    uint32_t lo = ((addr & 0x3FFFF) >> 4) | ((lbo >> 4) << 16);
    return ((uint64_t)0x40000040u << 32) | lo;
}
#define DOFF(bytes) ((uint64_t)((bytes) >> 4))

#define ACC64 "{%0, %1, %2, %3, %4, %5, %6, %7, %8, %9, %10, %11, %12, %13, %14, %15, " \
              "%16, %17, %18, %19, %20, %21, %22, %23, %24, %25, %26, %27, %28, %29, %30, %31, " \
              "%32, %33, %34, %35, %36, %37, %38, %39, %40, %41, %42, %43, %44, %45, %46, %47, " \
              "%48, %49, %50, %51, %52, %53, %54, %55, %56, %57, %58, %59, %60, %61, %62, %63}"
#define C8(c, d, o) c(d[o]), c(d[o + 1]), c(d[o + 2]), c(d[o + 3]), c(d[o + 4]), c(d[o + 5]), c(d[o + 6]), c(d[o + 7])
#define C64(c, d) C8(c, d, 0), C8(c, d, 8), C8(c, d, 16), C8(c, d, 24), C8(c, d, 32), C8(c, d, 40), C8(c, d, 48), C8(c, d, 56)

template <int TB> __device__ __forceinline__ void mma_ss(float (&d)[64], uint64_t da, uint64_t db) {
    asm volatile("wgmma.mma_async.sync.aligned.m64n128k16.f32.bf16.bf16 " ACC64 ", %64, %65, 1, 1, 1, 0, %66;"
                 : C64("+f", d) : "l"(da), "l"(db), "n"(TB));
}
template <int TB> __device__ __forceinline__ void mma_ss_init(float (&d)[64], uint64_t da, uint64_t db) {
    asm volatile("wgmma.mma_async.sync.aligned.m64n128k16.f32.bf16.bf16 " ACC64 ", %64, %65, 0, 1, 1, 0, %66;"
                 : C64("=f", d) : "l"(da), "l"(db), "n"(TB));
}
__device__ __forceinline__ void mma_ss_pred(float (&d)[64], uint64_t da, uint64_t db, int acc) {
    asm volatile("{\n.reg .pred p;\nsetp.ne.b32 p, %66, 0;\n"
                 "wgmma.mma_async.sync.aligned.m64n128k16.f32.bf16.bf16 " ACC64 ", %64, %65, p, 1, 1, 0, 1;\n}"
                 : C64("+f", d) : "l"(da), "l"(db), "r"(acc));
}
__device__ __forceinline__ void mma_rs(float (&d)[64], const uint32_t* a, uint64_t db, int acc) {
    asm volatile("{\n.reg .pred p;\nsetp.ne.b32 p, %69, 0;\n"
                 "wgmma.mma_async.sync.aligned.m64n128k16.f32.bf16.bf16 " ACC64 ", {%64, %65, %66, %67}, %68, p, 1, 1, 1;\n}"
                 : C64("+f", d) : "r"(a[0]), "r"(a[1]), "r"(a[2]), "r"(a[3]), "l"(db), "r"(acc));
}

#define TSTAMP(idx)

__device__ __forceinline__ void stage_tile(const float (&d)[64], float s0, float s1, uint32_t st_addr) {
#pragma unroll
    for (int j = 0; j < 8; j++) {
        uint32_t a = (st_addr + (j >> 2) * A_SLOT) ^ ((j & 3) * 32);
        stsm4(a, pack_bf16(d[8 * j] * s0, d[8 * j + 1] * s0), pack_bf16(d[8 * j + 2] * s1, d[8 * j + 3] * s1),
              pack_bf16(d[8 * j + 4] * s0, d[8 * j + 5] * s0), pack_bf16(d[8 * j + 6] * s1, d[8 * j + 7] * s1));
    }
}
__device__ __forceinline__ void stage_tile(const float (&d)[64], uint32_t st_addr) {
#pragma unroll
    for (int j = 0; j < 8; j++) {
        uint32_t a = (st_addr + (j >> 2) * A_SLOT) ^ ((j & 3) * 32);
        stsm4(a, pack_bf16(d[8 * j], d[8 * j + 1]), pack_bf16(d[8 * j + 2], d[8 * j + 3]),
              pack_bf16(d[8 * j + 4], d[8 * j + 5]), pack_bf16(d[8 * j + 6], d[8 * j + 7]));
    }
}

__device__ __forceinline__ void stash_tile(const float (&d)[64], char* dst) {
#pragma unroll
    for (int j = 0; j < 8; j++) {
        uint4 v = make_uint4(pack_bf16(d[8 * j], d[8 * j + 1]), pack_bf16(d[8 * j + 2], d[8 * j + 3]),
                             pack_bf16(d[8 * j + 4], d[8 * j + 5]), pack_bf16(d[8 * j + 6], d[8 * j + 7]));
        *(uint4*)(dst + (j >> 2) * A_SLOT + (j & 3) * 512) = v;
    }
}

__device__ __forceinline__ void stash_packed(const uint32_t (&p)[32], char* dst) {
#pragma unroll
    for (int j = 0; j < 8; j++)
        *(uint4*)(dst + (j >> 2) * A_SLOT + (j & 3) * 512) = make_uint4(p[4 * j], p[4 * j + 1], p[4 * j + 2], p[4 * j + 3]);
}
__device__ __forceinline__ void stage_packed(const uint32_t (&p)[32], uint32_t st_addr) {
#pragma unroll
    for (int j = 0; j < 8; j++) stsm4((st_addr + (j >> 2) * A_SLOT) ^ ((j & 3) * 32), p[4 * j], p[4 * j + 1], p[4 * j + 2], p[4 * j + 3]);
}

template <bool INIT>
__device__ __forceinline__ void gemm_step(float (&c)[64], uint64_t a, uint64_t b) {
    if (INIT) mma_ss_init<1>(c, a, b); else mma_ss<1>(c, a, b);
#pragma unroll
    for (int kk = 1; kk < 4; kk++) mma_ss<1>(c, a + DOFF(kk * 32), b + DOFF(kk * 2048));
}

template <int MODE>
__device__ __forceinline__ void gemm_phase1(float (&c0)[64], uint32_t sb, int wg, int lane, uint32_t& it, int nk, int acc = 0) {
    const uint64_t a0 = mk_desc(sb + OFF_A + wg * 8192, 16), b0 = mk_desc(sb + OFF_B, 8192);
    mbar_wait(sb + BAR_FULL, (it >> 2) & 1);
    wg_fence();
    if (MODE == 2) {
        mma_ss_pred(c0, a0, b0, acc);
#pragma unroll
        for (int kk = 1; kk < 4; kk++) mma_ss<1>(c0, a0 + DOFF(kk * 32), b0 + DOFF(kk * 2048));
    } else {
        gemm_step<MODE == 0>(c0, a0, b0);
    }
    wg_commit();
    it++;
#pragma unroll 1
    for (int ks = 1; ks < nk; ks++) {
        const uint32_t s = it & 3;
        mbar_wait(sb + BAR_FULL + s * 8, (it >> 2) & 1);
        wg_fence();
        gemm_step<false>(c0, a0 + s * (A_SLOT >> 4), b0 + s * (B_SLOT >> 4));
        wg_commit();
        wg_wait<1>();
        if (lane == 0) mbar_arrive(sb + BAR_EMPTY + ((it - 1) & 3) * 8);
        it++;
    }
    wg_wait<0>();
    reg_fence(c0);
    if (lane == 0) mbar_arrive(sb + BAR_EMPTY + 3 * 8);
}

__device__ __forceinline__ void gemm_phase2(float (&c0)[64], float (&c1)[64], uint32_t (&p)[32], uint32_t sb, int wg, int lane, uint32_t& it, int nk,
                                            char* base, uint32_t pend, uint32_t op, uint32_t staged) {
    const uint64_t a0 = mk_desc(sb + OFF_A + wg * 8192, 16), b0 = mk_desc(sb + OFF_B, 8192);
    const uint32_t ph0 = (it >> 2) & 1;
    mbar_wait(sb + BAR_FULL, ph0);
    wg_fence();
    gemm_step<true>(c0, a0, b0);
    wg_commit();
    mbar_wait(sb + BAR_FULL + 8, ph0);
    wg_fence();
    gemm_step<false>(c0, a0 + DOFF(A_SLOT), b0 + DOFF(B_SLOT));
    wg_commit();
    if (pend) {
        stash_packed(p, base + (size_t)pend * 2 * A_SLOT);
        __syncwarp();
        if (lane == 0) mbar_arrive(staged);
    }
    wg_fence();
    gemm_step<true>(c1, a0, b0 + DOFF(16384));
    wg_commit();
    gemm_step<false>(c1, a0 + DOFF(A_SLOT), b0 + DOFF(B_SLOT + 16384));
    wg_commit();
    wg_wait<1>();
    if (lane == 0) mbar_arrive(sb + BAR_EMPTY);
    it += 2;
#pragma unroll 1
    for (int ks = 2; ks < nk - 2; ks++) {
        const uint32_t s = it & 3;
        const uint64_t a = a0 + s * (A_SLOT >> 4), b = b0 + s * (B_SLOT >> 4);
        mbar_wait(sb + BAR_FULL + s * 8, (it >> 2) & 1);
        wg_fence();
#pragma unroll
        for (int kk = 0; kk < 4; kk++) {
            mma_ss<1>(c0, a + DOFF(kk * 32), b + DOFF(kk * 2048));
            mma_ss<1>(c1, a + DOFF(kk * 32), b + DOFF(16384 + kk * 2048));
        }
        wg_commit();
        wg_wait<1>();
        if (lane == 0) mbar_arrive(sb + BAR_EMPTY + ((it - 1) & 3) * 8);
        it++;
    }
    const uint32_t ph1 = (it >> 2) & 1;
    mbar_wait(sb + BAR_FULL + 16, ph1);
    wg_fence();
    gemm_step<false>(c0, a0 + DOFF(2 * A_SLOT), b0 + DOFF(2 * B_SLOT));
    wg_commit();
    wg_wait<1>();
    if (lane == 0) mbar_arrive(sb + BAR_EMPTY + 8);
    mbar_wait(sb + BAR_FULL + 24, ph1);
    wg_fence();
    gemm_step<false>(c0, a0 + DOFF(3 * A_SLOT), b0 + DOFF(3 * B_SLOT));
    wg_commit();
    gemm_step<false>(c1, a0 + DOFF(2 * A_SLOT), b0 + DOFF(2 * B_SLOT + 16384));
    gemm_step<false>(c1, a0 + DOFF(3 * A_SLOT), b0 + DOFF(3 * B_SLOT + 16384));
    wg_commit();
    wg_wait<1>();
    reg_fence(c0);
    if (op_type(op) == OP_OT) {
        float4* dst = g_park + op_tile(op) * (12 * 16 * 32) + (threadIdx.x >> 5) * (16 * 32) + lane;
#pragma unroll
        for (int j = 0; j < 16; j++) dst[j * 32] = make_float4(c0[4 * j], c0[4 * j + 1], c0[4 * j + 2], c0[4 * j + 3]);
        __syncwarp();
        if (lane == 0) mbar_arrive(staged);
    } else if (op & Q_ST0) {
        stash_tile(c0, base + (size_t)op_head(op) * 2 * A_SLOT);
    }
    wg_wait<0>();
    reg_fence(c1);
    if (lane == 0) { mbar_arrive(sb + BAR_EMPTY + 16); mbar_arrive(sb + BAR_EMPTY + 24); }
    it += 2;
}

__device__ __forceinline__ void qk_issue(float (&s)[64], uint64_t qa, uint64_t kb, int never) {
    mma_ss_init<0>(s, qa, kb);
#pragma unroll
    for (int kk = 1; kk < 8; kk++)
        mma_ss<0>(s, qa + DOFF((kk >> 2) * A_SLOT + (kk & 3) * 32), kb + DOFF((kk >> 2) * 16384 + (kk & 3) * 32));
}

__device__ __forceinline__ int imax3(float a, float b, float c) {
    return __vimax3_s32(__float_as_int(a), __float_as_int(b), __float_as_int(c));
}

__device__ __forceinline__ void softmax_block(float (&s)[64], uint32_t (&p)[32], float (&o)[64], float& m0, float& m1, float& l0, float& l1, int never, bool first) {
    constexpr float C = 0.08838834764831845f * 1.4426950408889634f;
    int i0 = imax3(s[0], s[1], s[4]), i1 = imax3(s[2], s[3], s[6]);
    int j0 = imax3(s[5], s[8], s[9]), j1 = imax3(s[7], s[10], s[11]);
#pragma unroll
    for (int j = 3; j < 15; j += 2) {
        i0 = imax3(__int_as_float(i0), s[4 * j], s[4 * j + 1]);
        i1 = imax3(__int_as_float(i1), s[4 * j + 2], s[4 * j + 3]);
        j0 = imax3(__int_as_float(j0), s[4 * j + 4], s[4 * j + 5]);
        j1 = imax3(__int_as_float(j1), s[4 * j + 6], s[4 * j + 7]);
    }
    i0 = imax3(__int_as_float(i0), s[60], s[61]);
    i1 = imax3(__int_as_float(i1), s[62], s[63]);
    i0 = imax3(__int_as_float(i0), __int_as_float(j0), m0);
    i1 = imax3(__int_as_float(i1), __int_as_float(j1), m1);
    i0 = max(i0, __shfl_xor_sync(0xffffffffu, i0, 1));
    i1 = max(i1, __shfl_xor_sync(0xffffffffu, i1, 1));
    i0 = max(i0, __shfl_xor_sync(0xffffffffu, i0, 2));
    i1 = max(i1, __shfl_xor_sync(0xffffffffu, i1, 2));
    float x0 = __int_as_float(i0), x1 = __int_as_float(i1);
    if (__any_sync(0xffffffffu, (i0 | i1) < 0)) {
        x0 = m0;
        x1 = m1;
#pragma unroll
        for (int j = 0; j < 16; j++) {
            x0 = fmaxf(x0, fmaxf(s[4 * j], s[4 * j + 1]));
            x1 = fmaxf(x1, fmaxf(s[4 * j + 2], s[4 * j + 3]));
        }
        x0 = fmaxf(x0, __shfl_xor_sync(0xffffffffu, x0, 1));
        x1 = fmaxf(x1, __shfl_xor_sync(0xffffffffu, x1, 1));
        x0 = fmaxf(x0, __shfl_xor_sync(0xffffffffu, x0, 2));
        x1 = fmaxf(x1, __shfl_xor_sync(0xffffffffu, x1, 2));
    }
    const float r0 = ex2((m0 - x0) * C), r1 = ex2((m1 - x1) * C);
    m0 = x0;
    m1 = x1;
    const float n0 = -x0 * C, n1 = -x1 * C;
    float t0 = l0 * r0, t1 = l1 * r1, u0 = 0.f, u1 = 0.f;
    constexpr int CH = SM_CH, NC = 32 / CH, LAG = SM_LAG;
#pragma unroll
    for (int c = -1; c < NC + LAG; c++) {
#pragma unroll
        for (int jj = 0; jj < CH; jj++) {
            if (c >= 0 && c < NC) {
                const int j = c * CH + jj;
                s[2 * j] = ex2(s[2 * j]); s[2 * j + 1] = ex2(s[2 * j + 1]);
                asm volatile("{\n.reg .pred p;\nsetp.lt.f32 p, %2, 0f3F800000;\n@p mul.f32 %0, %0, %2;\n@p mul.f32 %1, %1, %2;\n}" : "+f"(o[2 * j]), "+f"(o[2 * j + 1]) : "f"((j & 1) ? r1 : r0));
            }
            if (c + 1 < NC) {
                const int j = (c + 1) * CH + jj;
                s[2 * j] = fmaf(s[2 * j], C, (j & 1) ? n1 : n0); s[2 * j + 1] = fmaf(s[2 * j + 1], C, (j & 1) ? n1 : n0);
            }
            if (c >= LAG) {
                const int j = (c - LAG) * CH + jj;
                if (j & 1) { t1 += s[2 * j]; if (j == 1) u1 = s[3]; else u1 += s[2 * j + 1]; }
                else { t0 += s[2 * j]; if (j == 0) u0 = s[1]; else u0 += s[2 * j + 1]; }
                p[j] = pack_bf16(s[2 * j], s[2 * j + 1]);
            }
        }
        if (c >= 0 && c < NC - 1) {
#pragma unroll
            for (int i = 0; i < 64; i++) if (i >= 2 * (c - LAG + 1) * CH) asm volatile("" : "+f"(s[i]));
#pragma unroll
            for (int i = 0; i < 64; i++) asm volatile("" : "+f"(o[i]));
#pragma unroll
            for (int i = 0; i < 32; i++) if (i < (c - LAG + 1) * CH) asm volatile("" : "+r"(p[i]));
            asm volatile("" : "+f"(t0), "+f"(t1), "+f"(u0), "+f"(u1));
            SCHED_FENCE(never);
        }
    }
    l0 = t0 + u0;
    l1 = t1 + u1;
}

__device__ __forceinline__ void publish_tile(uint32_t bar, int lane) {
    fence_async_smem();
    __syncwarp();
    if (lane == 0) mbar_arrive(bar);
}
__device__ __forceinline__ void attn_epilogue(float (&o)[64], float l0, float l1, uint32_t st_addr) {
    l0 += __shfl_xor_sync(0xffffffffu, l0, 1);
    l1 += __shfl_xor_sync(0xffffffffu, l1, 1);
    l0 += __shfl_xor_sync(0xffffffffu, l0, 2);
    l1 += __shfl_xor_sync(0xffffffffu, l1, 2);
    stage_tile(o, __fdividef(1.f, l0), __fdividef(1.f, l1), st_addr);
}

__global__ void __launch_bounds__(NTHREADS, 1) mha2_kernel(const __grid_constant__ Params prm) {
    extern __shared__ __align__(1024) char smem_raw[];
    const uint32_t sb = smem_u32(smem_raw);
    const int tid = threadIdx.x, lane = tid & 31;
    const int warp = __shfl_sync(0xffffffffu, tid >> 5, 0);
    const int cta = blockIdx.x;

    if (tid == 384) {
        const uint32_t br0 = op_g(prm.ops[cta][0]) >> 3;
        asm volatile("prefetch.tensormap [%0];" ::"l"(&prm.x[br0]) : "memory");
        asm volatile("prefetch.tensormap [%0];" ::"l"(&prm.wq[br0]) : "memory");
        asm volatile("prefetch.tensormap [%0];" ::"l"(&prm.k[br0]) : "memory");
        asm volatile("prefetch.tensormap [%0];" ::"l"(&prm.v[br0]) : "memory");
    }
    if (tid == 0) {
        for (int i = 0; i < 4; i++) { mbar_init(sb + BAR_FULL + 8 * i, 1); mbar_init(sb + BAR_EMPTY + 8 * i, 12); }
        for (int i = 0; i < 2; i++) mbar_init(sb + BAR_QFREE + 8 * i, 3);
        for (int i = 0; i < 3; i++) { mbar_init(sb + BAR_STAGED + 8 * i, 4); mbar_init(sb + BAR_QREADY + 8 * i, 1); mbar_init(sb + BAR_QLOAD + 8 * i, 1); }
        asm volatile("fence.mbarrier_init.release.cluster;" ::: "memory");
    }
    __syncthreads();

    const uint16_t* ops = prm.ops[cta];

    if (warp >= 12) {
        asm volatile("setmaxnreg.dec.sync.aligned.u32 32;");
        const unsigned epoch = g_epoch[cta] + 1;
        if (warp == 12) {
            uint64_t pol;
            asm volatile("createpolicy.fractional.L2::evict_first.b64 %0, 1.0;" : "=l"(pol));
            uint32_t it = 0;
            bool after_att = false;
#pragma unroll 1
            for (int i = 0;; i++) {
                const uint32_t op = __shfl_sync(0xffffffffu, (uint32_t)ops[i], 0);
                const uint32_t ty = op_type(op), g = op_g(op), h = op_h(op), br = g >> 3;
                if (ty == OP_END) break;
                const uint32_t nx = __shfl_sync(0xffffffffu, (uint32_t)ops[i + 1], 0);
                if (ty == OP_AT) {
                    const int row0 = ((g & 7) * NH + h) * SK;
#pragma unroll 1
                    for (int t = 0; t < 16; t++, it++) {
                        const uint32_t s = it & 3;
                        mbar_wait_sleep(sb + BAR_EMPTY + s * 8, ((it >> 2) & 1) ^ 1);
                        if (elect_one()) {
                            mbar_expect_tx(sb + BAR_FULL + s * 8, B_SLOT);
                            tma_3d_hint(sb + OFF_B + s * B_SLOT, (t & 1) ? &prm.v[br] : &prm.k[br], 0, row0 + (t >> 1) * 128, 0,
                                        sb + BAR_FULL + s * 8, pol);
                            if (KPF > 0 && (t + KPF < 16 || op_type(nx) == OP_AT)) {
                                const uint32_t o2 = t + KPF < 16 ? op : nx;
                                tma_prefetch_3d_hint(((t + KPF) & 1) ? &prm.v[op_g(o2) >> 3] : &prm.k[op_g(o2) >> 3], 0, (op_head(o2) & 255) * SK + (((t + KPF) & 15) >> 1) * 128, 0, pol);
                            }
                        }
                    }
                    after_att = true;
                } else if (ty == OP_Q) {
                    const bool two = op & Q_TWO;
                    if (STAG > 0 && !two) { const long long c0 = clock64(); while (clock64() - c0 < (long long)(h * 4 + (g & 3)) * (STAG / 4)) __nanosleep(50); }
                    const bool pf = NPF > 0 && (PFALL || i == 0) && op_type(nx) == OP_AT;
#pragma unroll 1
                    for (int ks = 0; ks < 16; ks++, it++) {
                        const uint32_t s = it & 3;
                        if (after_att && (ks == 0 || ks == 2)) mbar_wait_sleep(sb + BAR_QFREE + ks * 4, 0);
                        mbar_wait_sleep(sb + BAR_EMPTY + s * 8, ((it >> 2) & 1) ^ 1);
                        if (elect_one()) {
                            mbar_expect_tx(sb + BAR_FULL + s * 8, two ? A_SLOT + B_SLOT : A_SLOT + B_SLOT / 2);
                            tma_2d(sb + OFF_A + s * A_SLOT, &prm.x[br], ks * 64, (g & 7) * SQ, sb + BAR_FULL + s * 8);
                            tma_3d(sb + OFF_B + s * B_SLOT, &prm.wq[br], 0, ks * 64, h * 2, sb + BAR_FULL + s * 8);
                            if (two) tma_3d(sb + OFF_B + s * B_SLOT + 16384, &prm.wq[br], 0, ks * 64, h * 2 + 2, sb + BAR_FULL + s * 8);
                            if (WQPF > 0 && i == 0 && ks >= WQS && (ks - WQS) % WQD == 0) {
                                const int id = (ks - WQS) / WQD * NCTA + cta;
                                if (id < 32 * WQPF) tma_prefetch_3d(&prm.wq[id & 1], 0, ((id >> 1) & 15) * 64, (14 + (id >> 5)) * 2);
                            }
                            if (pf && ks >= PFS && (ks - PFS) % PFD == 0 && (ks - PFS) / PFD < NPF) {
                                const int t = (ks - PFS) / PFD;
                                tma_prefetch_3d((t & 1) ? &prm.v[br] : &prm.k[br], 0, (op_head(nx) & 255) * SK + (t >> 1) * 128, 0);
                            }
                        }
                    }
                    after_att = false;
                } else {
                    const char* osrc = (const char*)g_o + (size_t)g * NH * 2 * A_SLOT;
                    const unsigned* flg = g_flag + g * NH;
                    const int k1 = op_k1(op), k0 = op_takeover(op) ? k1 : 0, col = (h & 3) * 4;
#pragma unroll 1
                    for (int ks = k0; ks < 64; ks++, it++) {
                        const uint32_t s = it & 3;
                        if (after_att && (ks == k0 || ks == k0 + 2)) mbar_wait_sleep(sb + BAR_QFREE + (ks - k0) * 4, 0);
                        mbar_wait_sleep(sb + BAR_EMPTY + s * 8, ((it >> 2) & 1) ^ 1);
                        if (elect_one()) {
                            mbar_expect_tx(sb + BAR_FULL + s * 8, ks < k1 ? A_SLOT + B_SLOT : A_SLOT + B_SLOT / 2);
                            tma_3d(sb + OFF_B + s * B_SLOT, &prm.wo[br], 0, ks * 64, (ks < k1 || k0) ? col : col + 2, sb + BAR_FULL + s * 8);
                            if (ks < k1) tma_3d(sb + OFF_B + s * B_SLOT + 16384, &prm.wo[br], 0, ks * 64, col + 2, sb + BAR_FULL + s * 8);
                        }
                        if ((ks & 1) == 0) {
                            flag_wait(flg + (ks >> 1), 3 * epoch);
                            asm volatile("fence.proxy.async.global;" ::: "memory");
                        }
                        if (elect_one()) bulk_load(sb + OFF_A + s * A_SLOT, osrc + (size_t)ks * A_SLOT, A_SLOT, sb + BAR_FULL + s * 8);
                    }
                }
            }
        } else {
            const int w = warp - 13;
            uint32_t nq = 0;
#pragma unroll 1
            for (int i = 0;; i++) {
                const uint32_t op = __shfl_sync(0xffffffffu, (uint32_t)ops[i], 0);
                const uint32_t ty = op_type(op);
                if (ty == OP_END) break;
                const uint32_t n1 = __shfl_sync(0xffffffffu, (uint32_t)ops[i + 1], 0);
                const bool more = op_type(n1) == OP_AT && !(n1 & AT_LAST);
                mbar_wait_sleep(sb + BAR_STAGED + w * 8, i & 1);
                if (lane == 0) {
                    if (ty == OP_Q) {
                        if (op & (Q_ST0 | Q_ST1)) {
                            __threadfence();
                            if (op & Q_ST0) asm volatile("st.relaxed.gpu.global.u32 [%0], %1;" ::"l"(g_qflag + op_head(op) * 4 + w), "r"(epoch) : "memory");
                            if (op & Q_ST1) asm volatile("st.relaxed.gpu.global.u32 [%0], %1;" ::"l"(g_qflag + op_head(op) * 4 + 4 + w), "r"(epoch) : "memory");
                        }
                        if (op_type(n1) == OP_AT && (n1 & AT_LAST)) mbar_arrive(sb + BAR_QFREE + ((n1 & AT_BUF1) ? 0 : 8));
                    } else if (ty == OP_AT) {
                        char* dst = (char*)g_o + (size_t)op_head(op) * 2 * A_SLOT + w * 8192;
                        const uint32_t src = sb + OFF_A + ((op & AT_BUF1) ? 2 * A_SLOT : 0) + w * 8192;
                        bulk_store(dst, src, 8192);
                        bulk_store(dst + A_SLOT, src + A_SLOT, 8192);
                        asm volatile("cp.async.bulk.commit_group;" ::: "memory");
                        if (!more) {
                            asm volatile("cp.async.bulk.wait_group.read 0;" ::: "memory");
                            mbar_arrive(sb + BAR_QFREE + ((op & AT_BUF1) ? 8 : 0));
                        }
                        asm volatile("cp.async.bulk.wait_group 0;" ::: "memory");
                        asm volatile("fence.proxy.async;" ::: "memory");
                        asm volatile("red.release.gpu.global.add.u32 [%0], 1;" ::"l"(g_flag + op_head(op)) : "memory");
                    } else {
                        if (!op_takeover(op)) {
                            __threadfence();
                            asm volatile("st.relaxed.gpu.global.u32 [%0], %1;" ::"l"(g_pflag + op_tile(op) * 4 + w), "r"(epoch) : "memory");
                            mbar_wait_sleep(sb + BAR_STAGED + w * 8, ~i & 1);
                        }
                        const int c0 = (op_g(op) >> 3) * DM + (op_h(op) & 3) * 256 + (op_takeover(op) ? 0 : 128), r0 = (op_g(op) & 7) * SQ + w * 64;
                        tma_store_2d(&prm.out, sb + OFF_A + w * 8192, c0, r0);
                        tma_store_2d(&prm.out, sb + OFF_A + A_SLOT + w * 8192, c0 + 64, r0);
                        asm volatile("cp.async.bulk.commit_group;" ::: "memory");
                        asm volatile("cp.async.bulk.wait_group 0;" ::: "memory");
                    }
                }
                __syncwarp();
                if (!more) continue;
                const uint32_t n2 = __shfl_sync(0xffffffffu, (uint32_t)ops[i + 2], 0);
                if (!(n2 & AT_STASH)) continue;
                const uint32_t buf = sb + OFF_A + ((n2 & AT_BUF1) ? 2 * A_SLOT : 0) + w * 8192;
                if (lane == 0) {
                    flag_wait(g_qflag + op_head(n2) * 4 + w, epoch);
                    asm volatile("fence.proxy.async;" ::: "memory");
                    const char* src = (const char*)g_o + (size_t)op_head(n2) * 2 * A_SLOT + w * 8192;
                    mbar_expect_tx(sb + BAR_QLOAD + w * 8, 16384);
                    bulk_load(buf, src, 8192, sb + BAR_QLOAD + w * 8);
                    bulk_load(buf + A_SLOT, src + A_SLOT, 8192, sb + BAR_QLOAD + w * 8);
                }
                __syncwarp();
                mbar_wait_sleep(sb + BAR_QLOAD + w * 8, nq);
                nq ^= 1;
#pragma unroll 1
                for (int c = 0; c < 8; c++) {
                    const uint32_t blk = buf + (c >> 2) * A_SLOT + (c & 3) * 2048;
                    uint32_t v[16];
#pragma unroll
                    for (int j = 0; j < 4; j++)
                        asm volatile("ld.shared.v4.u32 {%0, %1, %2, %3}, [%4];"
                                     : "=r"(v[4 * j]), "=r"(v[4 * j + 1]), "=r"(v[4 * j + 2]), "=r"(v[4 * j + 3]) : "r"(blk + lane * 16 + j * 512) : "memory");
                    __syncwarp();
                    const uint32_t st = blk + (lane & 15) * 128 + (((lane >> 4) ^ (lane & 7)) << 4);
#pragma unroll
                    for (int j = 0; j < 4; j++) stsm4(st ^ (j * 32), v[4 * j], v[4 * j + 1], v[4 * j + 2], v[4 * j + 3]);
                }
                asm volatile("fence.proxy.async;" ::: "memory");
                __syncwarp();
                if (lane == 0) mbar_arrive(sb + BAR_QREADY + w * 8);
            }
        }
        asm volatile("bar.sync 4, 128;" ::: "memory");
        if (tid == 384) g_epoch[cta] = epoch;
    } else {
        asm volatile("setmaxnreg.inc.sync.aligned.u32 160;");
        const int wg = warp >> 2;
        const int my_bar = 1 + wg, next_bar = wg == 2 ? 1 : 2 + wg;
        const uint32_t qa0 = sb + OFF_A + wg * 8192;
        const uint32_t st_addr = qa0 + ((warp & 3) * 16 + (lane & 15)) * 128 + (((lane >> 4) ^ (lane & 7)) << 4);
        const uint32_t staged = sb + BAR_STAGED + wg * 8;
        const uint64_t qd0 = mk_desc(qa0, 16), kd0 = mk_desc(sb + OFF_B, 16), vd0 = mk_desc(sb + OFF_B, 16384);
        float o[64], s[64];
        uint32_t p[32];
        uint32_t it = 0, pend = 0;
        int i = 0;
#pragma unroll
        for (int j = 0; j < 32; j++) p[j] = 0;
        TSTAMP(0);
#pragma unroll 1
        for (;;) {
            const uint32_t op = __shfl_sync(0xffffffffu, (uint32_t)ops[i], 0);
            if (op_type(op) == OP_END) break;
            if (op_type(op) != OP_AT) {
                if (op_type(op) == OP_Q && !(op & Q_TWO)) {
                    gemm_phase1<0>(o, sb, wg, lane, it, 16);
                    stage_tile(o, st_addr + 2 * A_SLOT);
                    publish_tile(staged, lane);
                } else if (op_type(op) == OP_OT && op_takeover(op)) {
                    const int n1 = 56 - op_k1(op);
#pragma unroll
                    for (int j = 0; j < 64; j++) s[j] = 0.f;
                    reg_fence(s);
                    if (n1 > 0) gemm_phase1<1>(s, sb, wg, lane, it, n1);
                    flag_wait(g_pflag + op_tile(op) * 4 + wg, g_epoch[cta] + 1);
                    const float4* src = g_park + op_tile(op) * (12 * 16 * 32) + (tid >> 5) * (16 * 32) + lane;
#pragma unroll
                    for (int j = 0; j < 16; j++) {
                        const float4 v = __ldcg(src + j * 32);
                        o[4 * j] = v.x; o[4 * j + 1] = v.y; o[4 * j + 2] = v.z; o[4 * j + 3] = v.w;
                    }
                    gemm_phase1<1>(s, sb, wg, lane, it, 8);
#pragma unroll
                    for (int j = 0; j < 64; j++) s[j] += o[j];
                    stage_tile(s, st_addr);
                    publish_tile(staged, lane);
                    TSTAMP(i + 1);
                    break;
                } else {
                    char* base = (char*)g_o + (tid >> 5) * 2048 + lane * 16;
                    char* dst = base + (size_t)op_head(op) * 2 * A_SLOT;
                    gemm_phase2(o, s, p, sb, wg, lane, it, op_type(op) == OP_Q ? 16 : op_k1(op), base, pend, op, staged);
                    if (op_type(op) == OP_OT) {
                        gemm_phase1<1>(s, sb, wg, lane, it, 64 - op_k1(op));
                        stage_tile(s, st_addr);
                        publish_tile(staged, lane);
                        TSTAMP(i + 1);
                        break;
                    }
#pragma unroll
                    for (int j = 0; j < 32; j++) p[j] = pack_bf16(s[2 * j], s[2 * j + 1]);
                    pend = 0;
                    if ((op & (Q_ST0 | Q_ST1)) == (Q_ST0 | Q_ST1)) {
                        pend = op_head(op) + 1;
                    } else {
                        if (!(op & Q_ST0)) stage_tile(o, st_addr);
                        if (op & Q_ST1) stash_packed(p, dst + 2 * A_SLOT); else stage_packed(p, st_addr + 2 * A_SLOT);
                        publish_tile(staged, lane);
                    }
                }
                i++;
                TSTAMP(i);
                continue;
            }
            float m0 = -INFINITY, m1 = -INFINITY, l0 = 0.f, l1 = 0.f;
            int t = (op & AT_BUF1) ? 8 : 0, tend = t + 8;
            const int tst = ((op & AT_LAST) || (ops[i + 1] & AT_STASH)) ? t + 8 : t + 16;
            while (!(ops[i++] & AT_LAST)) tend += 8;
            t = __shfl_sync(0xffffffffu, t, 0);
            tend = __shfl_sync(0xffffffffu, tend | (tst << 8), 0);
            const int tfirst = t + 1;
            if (wg == 2) bar_arrive(1);
            mbar_wait(sb + BAR_FULL, (it >> 2) & 1);
            bar_sync(my_bar);
            wg_fence();
            qk_issue(s, qd0 + (t & 8) * (2 * A_SLOT / 128), kd0, prm.never);
            wg_commit();
            bar_arrive(next_bar);
            wg_wait<0>();
            reg_fence(s);
            if (lane == 0) mbar_arrive(sb + BAR_EMPTY);
            it++;
            softmax_block(s, p, o, m0, m1, l0, l1, prm.never, true);
#pragma unroll 1
            for (t++; t != (tend & 255); t++) {
                const bool flip = (t & 7) == 0;
                if (flip && t >= (tend >> 8)) mbar_wait(sb + BAR_QREADY + wg * 8, ((t - (tend >> 8)) >> 3) & 1);
                const uint32_t sv = it & 3, sk = (it + 1) & 3;
                const uint64_t vb = vd0 + sv * (B_SLOT >> 4), kb = kd0 + sk * (B_SLOT >> 4), qd = qd0 + (t & 8) * (2 * A_SLOT / 128);
                TR(t & 15, 0);
                mbar_wait(sb + BAR_FULL + sv * 8, (it >> 2) & 1);
                bar_sync(my_bar);
                TR(t & 15, 1);
                wg_fence();
                mma_rs(o, p, vb, (t & 7) != 1);
#pragma unroll
                for (int kk = 1; kk < 7; kk++) mma_rs(o, p + 4 * kk, vb + DOFF(kk * 2048), 1);
                wg_commit();
                mma_rs(o, p + 28, vb + DOFF(7 * 2048), 1);
                wg_commit();
                TR(t & 15, 2);
                mbar_wait(sb + BAR_FULL + sk * 8, ((it + 1) >> 2) & 1);
                wg_wait<1>();
                TR(t & 15, 3);
                qk_issue(s, qd, kb, prm.never);
                wg_commit();
                bar_arrive(next_bar);
                TR(t & 15, 4);
                wg_wait<1>();
                reg_fence(o);
                if (lane == 0) mbar_arrive(sb + BAR_EMPTY + sv * 8);
                if ((t & 7) == 1 && t > tfirst) publish_tile(staged, lane);
                if (flip) {
                    attn_epilogue(o, l0, l1, st_addr + (~t & 8) * (2 * A_SLOT / 8));
                    m0 = m1 = -INFINITY;
                    l0 = l1 = 0.f;
                    TSTAMP(i - (((tend & 255) - t) >> 3));
                }
                wg_wait<0>();
                reg_fence(s);
                TR(t & 15, 5);
                if (lane == 0) mbar_arrive(sb + BAR_EMPTY + sk * 8);
                it += 2;
                softmax_block(s, p, o, m0, m1, l0, l1, prm.never, flip);
            }
            {
                const uint64_t vb = vd0 + DOFF(3 * B_SLOT);
                mbar_wait(sb + BAR_FULL + 3 * 8, (it >> 2) & 1);
                bar_sync(my_bar);
                wg_fence();
#pragma unroll
                for (int kk = 0; kk < 8; kk++) mma_rs(o, p + 4 * kk, vb + DOFF(kk * 2048), 1);
                wg_commit();
                if (wg != 2) bar_arrive(next_bar);
                wg_wait<0>();
                reg_fence(o);
                if (lane == 0) mbar_arrive(sb + BAR_EMPTY + 3 * 8);
                it++;
                attn_epilogue(o, l0, l1, st_addr + (~t & 8) * (2 * A_SLOT / 8));
                publish_tile(staged, lane);
                TSTAMP(i);
            }
        }
    }
}

void build_schedule(uint16_t (*ops)[MAXOPS]) {
    for (int c = 0; c < NCTA; c++) for (int j = 0; j < MAXOPS; j++) ops[c][j] = OP_END;
    auto mk = [](uint32_t ty, int g, int h, uint32_t fl) { return (uint16_t)(ty | (g << 2) | (h << 6) | fl); };
    auto ncta = [](int g, int j) { return CTA_N(g, j); };
    auto mcta = [](int g, int j) { return CTA_M(g, j); };
    const uint32_t QS = Q_TWO | Q_ST0 | Q_ST1;
    for (int g = 0; g < 16; g++) {
        const int q = g & 3, e = 128 + (g >> 2);
        int hn[7][4], hx[2];
        int h = 6;
        const int pos0 = q == 0 ? 1 : q == 1 ? 2 : q == 2 ? 4 : 3, pos1 = q == 0 ? 1 : q == 1 ? 3 : q == 2 ? 6 : 3;
        for (int w = 1; w < 7; w++) {
            if (pos0 == w) hx[0] = h++;
            if (pos1 == w) hx[1] = h++;
            for (int j = 0; j < 4; j++) hn[w][j] = h++;
        }
        for (int j = 0; j < 4; j++) {
            uint16_t* o = ops[ncta(g, j)];
            o[0] = mk(OP_Q, g, j, 0);
            o[1] = mk(OP_AT, g, j, AT_BUF1);
            for (int w = 1; w < 7; w++) o[w + 1] = mk(OP_AT, g, hn[w][j], AT_STASH | ((w & 1) ? 0 : AT_BUF1) | (w == 6 ? AT_LAST : 0));
            if (q != 3 || j != 1) {
                o[8] = mk(OP_OT, g, 4 | j, (K1N / 4) << 11);
                ops[mcta(g, j)][4] = mk(OP_OT, g, j, (K1N / 4) << 11);
            }
        }
        uint16_t* oe = ops[e];
        {
            uint16_t* o = ops[mcta(g, 0)];
            const int s0 = S0MODE == 0 ? (g & 1) : S0MODE == 1 ? 1 : ((g & 3) != 0);
            o[s0] = mk(OP_Q, g, 4, Q_TWO);
            o[s0 + 1] = mk(OP_AT, g, 4, 0);
            o[s0 + 2] = mk(OP_AT, g, 5, AT_BUF1 | AT_LAST);
        }
        if (q == 0) oe[0] = mk(OP_Q, g, hx[0], Q_TWO);
        if (q < 3) {
            oe[2 * q + 1] = mk(OP_AT, g, hx[0], q ? AT_STASH : 0);
            oe[2 * q + 2] = mk(OP_AT, g, hx[1], (q ? AT_STASH : 0) | AT_BUF1 | (q == 2 ? AT_LAST : 0));
        } else {
            uint16_t* o = ops[mcta(g, 1)];
            o[2] = mk(OP_Q, g, hx[0], Q_TWO);
            o[3] = mk(OP_AT, g, hx[0], 0);
            o[4] = mk(OP_AT, g, hx[1], AT_BUF1 | AT_LAST);
            o[5] = mk(OP_OT, g, 1, (K1E / 4) << 11);
            oe[7] = mk(OP_OT, g, 4 | 1, (K1E / 4) << 11);
        }
        int nq = 6;
        for (int sl = 0; sl < 4; sl++)
            for (int j = 0; j < 4; j++) {
                uint16_t* o = ops[mcta(g, j)];
                if (o[sl] == OP_END) {
                    if ((q == 0 || q == 3) && nq == hx[0]) nq += 2;
                    o[sl] = nq < 32 ? mk(OP_Q, g, nq, QS) : mk(OP_Q, g + 3, 30, QS);
                    nq += 2;
                }
            }
    }
}

typedef CUresult (*EncodeFn)(CUtensorMap*, CUtensorMapDataType, cuuint32_t, void*, const cuuint64_t*, const cuuint64_t*,
                             const cuuint32_t*, const cuuint32_t*, CUtensorMapInterleave, CUtensorMapSwizzle,
                             CUtensorMapL2promotion, CUtensorMapFloatOOBfill);

void encode(EncodeFn fn, CUtensorMap* m, void* ptr, int rank, const cuuint64_t* dims, const cuuint64_t* strides, const cuuint32_t* box) {
    const cuuint32_t es[3] = {1, 1, 1};
    fn(m, CU_TENSOR_MAP_DATA_TYPE_BFLOAT16, rank, ptr, dims, strides, box, es, CU_TENSOR_MAP_INTERLEAVE_NONE,
       CU_TENSOR_MAP_SWIZZLE_128B, CU_TENSOR_MAP_L2_PROMOTION_L2_128B, CU_TENSOR_MAP_FLOAT_OOB_FILL_NONE);
}

}

extern "C" void kernel_launch(void* const* d_in, const int* in_sizes, int n_in, void* d_out, int out_size) {
    static EncodeFn fn = nullptr;
    if (!fn) {
        cudaDriverEntryPointQueryResult qr;
        void* p = nullptr;
        cudaGetDriverEntryPoint("cuTensorMapEncodeTiled", &p, cudaEnableDefault, &qr);
        fn = (EncodeFn)p;
        cudaFuncSetAttribute(mha2_kernel, cudaFuncAttributeMaxDynamicSharedMemorySize, SMEM_BYTES);
    }
    Params prm;
    for (int br = 0; br < 2; br++) {
        void* x = d_in[5 * br + 0];
        void* k = d_in[5 * br + 1];
        void* v = d_in[5 * br + 2];
        void* wq = d_in[5 * br + 3];
        void* wo = d_in[5 * br + 4];
        {
            cuuint64_t dims[2] = {DM, NB * SQ}, st[1] = {DM * 2};
            cuuint32_t box[2] = {64, SQ};
            encode(fn, &prm.x[br], x, 2, dims, st, box);
        }
        {
            cuuint64_t dims[3] = {64, DM, NH * DH / 64}, st[2] = {NH * DH * 2, 128};
            cuuint32_t box[3] = {64, 64, 2};
            encode(fn, &prm.wq[br], wq, 3, dims, st, box);
        }
        {
            cuuint64_t dims[3] = {64, (cuuint64_t)NB * NH * SK, 2}, st[2] = {DH * 2, 128};
            cuuint32_t box[3] = {64, 128, 2};
            encode(fn, &prm.k[br], k, 3, dims, st, box);
            encode(fn, &prm.v[br], v, 3, dims, st, box);
        }
        {
            cuuint64_t dims[3] = {64, NH * DH, DM / 64}, st[2] = {DM * 2, 128};
            cuuint32_t box[3] = {64, 64, 2};
            encode(fn, &prm.wo[br], wo, 3, dims, st, box);
        }
    }
    {
        cuuint64_t dims[2] = {2 * DM, NB * SQ}, st[1] = {2 * DM * 2};
        cuuint32_t box[2] = {64, 64};
        encode(fn, &prm.out, d_out, 2, dims, st, box);
    }
    prm.never = 0;
    build_schedule(prm.ops);
    mha2_kernel<<<NCTA, NTHREADS, SMEM_BYTES>>>(prm);
}
```

```cpp
#include <cuda_runtime.h>
#include <cuda_bf16.h>
#include <cuda.h>
#include <stdint.h>

#define K1N 56
#define K1E 34
#define S0MODE 2
#define PUB 1

namespace {

constexpr int NB = 8, SQ = 192, DM = 1024, NH = 32, SK = 1024, DH = 128;
constexpr int NCTA = 132;
constexpr int MAXOPS = 10;
constexpr int NTHREADS = 512;

constexpr uint32_t A_SLOT = 24576;
constexpr uint32_t B_SLOT = 32768;
constexpr uint32_t OFF_A = 0;
constexpr uint32_t OFF_B = 4 * A_SLOT;
constexpr uint32_t OFF_BAR = OFF_B + 4 * B_SLOT;
constexpr uint32_t BAR_FULL = OFF_BAR;
constexpr uint32_t BAR_EMPTY = OFF_BAR + 32;
constexpr uint32_t BAR_QFREE = OFF_BAR + 64;
constexpr uint32_t BAR_STAGED = OFF_BAR + 80;
constexpr uint32_t BAR_QREADY = OFF_BAR + 104;
constexpr uint32_t BAR_QLOAD = OFF_BAR + 128;
constexpr uint32_t SMEM_BYTES = OFF_BAR + 256;

struct Params {
    CUtensorMap x[2], wq[2], k[2], v[2], wo[2];
    char* out;
    int never;
    uint16_t ops[NCTA][MAXOPS];
};

enum : uint32_t { OP_END = 0, OP_Q = 1, OP_AT = 2, OP_OT = 3 };
enum : uint32_t { Q_TWO = 1u << 11, Q_STASH = 1u << 12,
                  AT_STASH = 1u << 11, AT_BUF1 = 1u << 12, AT_LAST = 1u << 13 };
__host__ __device__ constexpr uint32_t op_type(uint32_t op) { return op & 3; }
__host__ __device__ constexpr uint32_t op_g(uint32_t op) { return (op >> 2) & 15; }
__host__ __device__ constexpr uint32_t op_h(uint32_t op) { return (op >> 6) & 31; }
__host__ __device__ constexpr uint32_t op_head(uint32_t op) { return op_g(op) * NH + op_h(op); }
__host__ __device__ constexpr uint32_t op_k1(uint32_t op) { return (op >> 11) * 2; }
__host__ __device__ constexpr bool op_takeover(uint32_t op) { return (op >> 8) & 1; }
__host__ __device__ constexpr uint32_t op_tile(uint32_t op) { return op_g(op) * 4 + ((op >> 6) & 3); }

__device__ uint4 g_o[2 * NB * NH * 2 * (A_SLOT / 16)];
__device__ float4 g_park[64 * 12 * 16 * 32];
__device__ unsigned g_flag[2 * NB * NH];
__device__ unsigned g_qflag[2 * NB * NH * 4];
__device__ unsigned g_pflag[64];
__device__ unsigned g_epoch[NCTA];

#define HSTAMP(idx)
#define TSTAMP(idx)

__device__ __forceinline__ uint32_t smem_u32(const void* p) { return (uint32_t)__cvta_generic_to_shared(p); }
__device__ __forceinline__ void mbar_init(uint32_t bar, uint32_t cnt) {
    asm volatile("mbarrier.init.shared::cta.b64 [%0], %1;" ::"r"(bar), "r"(cnt) : "memory");
}
__device__ __forceinline__ void mbar_expect_tx(uint32_t bar, uint32_t bytes) {
    asm volatile("mbarrier.arrive.expect_tx.shared::cta.b64 _, [%0], %1;" ::"r"(bar), "r"(bytes) : "memory");
}
__device__ __forceinline__ void mbar_arrive(uint32_t bar) {
    asm volatile("mbarrier.arrive.shared::cta.b64 _, [%0];" ::"r"(bar) : "memory");
}
__device__ __forceinline__ void mbar_wait(uint32_t bar, uint32_t parity) {
    asm volatile(
        "{\n.reg .pred p;\n.reg .u32 n;\nmov.u32 n, 0;\n"
        "LAB_WAIT:\n"
        "mbarrier.try_wait.parity.shared::cta.b64 p, [%0], %1;\n"
        "@p bra LAB_DONE;\n"
        "add.u32 n, n, 1;\nsetp.lt.u32 p, n, 0x2000000;\n@p bra LAB_WAIT;\ntrap;\n"
        "LAB_DONE:\n}" ::"r"(bar), "r"(parity) : "memory");
}
__device__ __forceinline__ void mbar_wait_sleep(uint32_t bar, uint32_t parity) {
    asm volatile(
        "{\n.reg .pred p;\n.reg .u32 n;\nmov.u32 n, 0;\n"
        "LAB_WAIT:\n"
        "mbarrier.try_wait.parity.shared::cta.b64 p, [%0], %1, 20000;\n"
        "@p bra LAB_DONE;\n"
        "add.u32 n, n, 1;\nsetp.lt.u32 p, n, 0x20000;\n@p bra LAB_WAIT;\ntrap;\n"
        "LAB_DONE:\n}" ::"r"(bar), "r"(parity) : "memory");
}
__device__ __forceinline__ void flag_wait(const unsigned* p, unsigned target) {
    asm volatile(
        "{\n.reg .pred p;\n.reg .u32 n, v;\n.reg .s32 d;\nmov.u32 n, 0;\n"
        "LAB_WAIT:\n"
        "ld.acquire.gpu.global.u32 v, [%0];\n"
        "sub.s32 d, v, %1;\nsetp.ge.s32 p, d, 0;\n"
        "@p bra LAB_DONE;\n"
        "nanosleep.u32 64;\n"
        "add.u32 n, n, 1;\nsetp.lt.u32 p, n, 0x400000;\n@p bra LAB_WAIT;\ntrap;\n"
        "LAB_DONE:\n}" ::"l"(p), "r"(target) : "memory");
}
__device__ __forceinline__ uint32_t flag_wait_any(const unsigned* p, unsigned target, uint32_t mask) {
    uint32_t r;
    asm volatile(
        "{\n.reg .pred p;\n.reg .u32 n, v;\n.reg .s32 d;\nmov.u32 n, 0;\n"
        "LAB_WAIT:\n"
        "ld.acquire.gpu.global.u32 v, [%1];\n"
        "sub.s32 d, v, %2;\nsetp.ge.s32 p, d, 0;\n"
        "vote.sync.ballot.b32 %0, p, 0xffffffff;\n"
        "and.b32 v, %0, %3;\nsetp.ne.u32 p, v, 0;\n"
        "@p bra LAB_DONE;\n"
        "nanosleep.u32 32;\n"
        "add.u32 n, n, 1;\nsetp.lt.u32 p, n, 0x400000;\n@p bra LAB_WAIT;\ntrap;\n"
        "LAB_DONE:\n}" : "=&r"(r) : "l"(p), "r"(target), "r"(mask) : "memory");
    return r;
}
__device__ __forceinline__ uint64_t policy_evict_first() {
    uint64_t r;
    asm("createpolicy.fractional.L2::evict_first.b64 %0, 1.0;" : "=l"(r));
    return r;
}
__device__ __forceinline__ void tma_2d(uint32_t dst, const CUtensorMap* m, int c0, int c1, uint32_t bar) {
    asm volatile("cp.async.bulk.tensor.2d.shared::cluster.global.mbarrier::complete_tx::bytes [%0], [%1, {%3, %4}], [%2];"
                 ::"r"(dst), "l"(m), "r"(bar), "r"(c0), "r"(c1) : "memory");
}
__device__ __forceinline__ void tma_3d(uint32_t dst, const CUtensorMap* m, int c0, int c1, int c2, uint32_t bar) {
    asm volatile("cp.async.bulk.tensor.3d.shared::cluster.global.mbarrier::complete_tx::bytes [%0], [%1, {%3, %4, %5}], [%2];"
                 ::"r"(dst), "l"(m), "r"(bar), "r"(c0), "r"(c1), "r"(c2) : "memory");
}
__device__ __forceinline__ void tma_3d_stream(uint32_t dst, const CUtensorMap* m, int c0, int c1, int c2, uint32_t bar) {
    asm volatile("cp.async.bulk.tensor.3d.shared::cluster.global.mbarrier::complete_tx::bytes.L2::cache_hint [%0], [%1, {%3, %4, %5}], [%2], %6;"
                 ::"r"(dst), "l"(m), "r"(bar), "r"(c0), "r"(c1), "r"(c2), "l"(policy_evict_first()) : "memory");
}
__device__ __forceinline__ void tma_prefetch_3d(const CUtensorMap* m, int c0, int c1, int c2) {
    asm volatile("cp.async.bulk.prefetch.tensor.3d.L2.global [%0, {%1, %2, %3}];" ::"l"(m), "r"(c0), "r"(c1), "r"(c2) : "memory");
}
__device__ __forceinline__ void bulk_load(uint32_t dst, const void* src, uint32_t bytes, uint32_t bar) {
    asm volatile("cp.async.bulk.shared::cluster.global.mbarrier::complete_tx::bytes [%0], [%1], %2, [%3];"
                 ::"r"(dst), "l"(src), "r"(bytes), "r"(bar) : "memory");
}
__device__ __forceinline__ void bulk_load_stream(uint32_t dst, const void* src, uint32_t bytes, uint32_t bar) {
    asm volatile("cp.async.bulk.shared::cluster.global.mbarrier::complete_tx::bytes.L2::cache_hint [%0], [%1], %2, [%3], %4;"
                 ::"r"(dst), "l"(src), "r"(bytes), "r"(bar), "l"(policy_evict_first()) : "memory");
}
__device__ __forceinline__ void bulk_store_stream(void* dst, uint32_t src, uint32_t bytes) {
    asm volatile("cp.async.bulk.global.shared::cta.bulk_group.L2::cache_hint [%0], [%1], %2, %3;"
                 ::"l"(dst), "r"(src), "r"(bytes), "l"(policy_evict_first()) : "memory");
}
__device__ __forceinline__ bool elect_one() {
    uint32_t r;
    asm volatile("{\n.reg .pred p;\nelect.sync _|p, 0xffffffff;\nselp.b32 %0, 1, 0, p;\n}" : "=r"(r));
    return r;
}
__device__ __forceinline__ void wg_fence() { asm volatile("wgmma.fence.sync.aligned;" ::: "memory"); }
__device__ __forceinline__ void wg_commit() { asm volatile("wgmma.commit_group.sync.aligned;" ::: "memory"); }
template <int N> __device__ __forceinline__ void wg_wait() { asm volatile("wgmma.wait_group.sync.aligned %0;" ::"n"(N) : "memory"); }
__device__ __forceinline__ void bar_sync(int id) { asm volatile("bar.sync %0, 256;" ::"r"(id) : "memory"); }
__device__ __forceinline__ void bar_arrive(int id) { asm volatile("bar.arrive %0, 256;" ::"r"(id) : "memory"); }
__device__ __forceinline__ float ex2(float x) { float y; asm("ex2.approx.ftz.f32 %0, %1;" : "=f"(y) : "f"(x)); return y; }
__device__ __forceinline__ uint32_t pack_bf16(float lo, float hi) {
    uint32_t r; asm("cvt.rn.bf16x2.f32 %0, %1, %2;" : "=r"(r) : "f"(hi), "f"(lo)); return r;
}
__device__ __forceinline__ void stsm4(uint32_t addr, uint32_t a, uint32_t b, uint32_t c, uint32_t d) {
    asm volatile("stmatrix.sync.aligned.m8n8.x4.shared.b16 [%0], {%1, %2, %3, %4};" ::"r"(addr), "r"(a), "r"(b), "r"(c), "r"(d) : "memory");
}
template <int N> __device__ __forceinline__ void reg_fence(float (&d)[N]) {
#pragma unroll
    for (int i = 0; i < N; i++) asm volatile("" : "+f"(d[i])::"memory");
}
#define SCHED_FENCE(x) asm volatile("{\n.reg .pred p;\nsetp.ne.s32 p, %0, 0;\n@p exit;\n}" ::"r"(x))

__device__ __forceinline__ uint64_t mk_desc(uint32_t addr, uint32_t lbo) {
    uint32_t lo = ((addr & 0x3FFFF) >> 4) | ((lbo >> 4) << 16);
    return ((uint64_t)0x40000040u << 32) | lo;
}
#define DOFF(bytes) ((uint64_t)((bytes) >> 4))

#define ACC64 "{%0, %1, %2, %3, %4, %5, %6, %7, %8, %9, %10, %11, %12, %13, %14, %15, " \
              "%16, %17, %18, %19, %20, %21, %22, %23, %24, %25, %26, %27, %28, %29, %30, %31, " \
              "%32, %33, %34, %35, %36, %37, %38, %39, %40, %41, %42, %43, %44, %45, %46, %47, " \
              "%48, %49, %50, %51, %52, %53, %54, %55, %56, %57, %58, %59, %60, %61, %62, %63}"
#define C8(c, d, o) c(d[o]), c(d[o + 1]), c(d[o + 2]), c(d[o + 3]), c(d[o + 4]), c(d[o + 5]), c(d[o + 6]), c(d[o + 7])
#define C64(c, d) C8(c, d, 0), C8(c, d, 8), C8(c, d, 16), C8(c, d, 24), C8(c, d, 32), C8(c, d, 40), C8(c, d, 48), C8(c, d, 56)

template <int TB> __device__ __forceinline__ void mma_ss(float (&d)[64], uint64_t da, uint64_t db) {
    asm volatile("wgmma.mma_async.sync.aligned.m64n128k16.f32.bf16.bf16 " ACC64 ", %64, %65, 1, 1, 1, 0, %66;"
                 : C64("+f", d) : "l"(da), "l"(db), "n"(TB));
}
template <int TB> __device__ __forceinline__ void mma_ss_init(float (&d)[64], uint64_t da, uint64_t db) {
    asm volatile("wgmma.mma_async.sync.aligned.m64n128k16.f32.bf16.bf16 " ACC64 ", %64, %65, 0, 1, 1, 0, %66;"
                 : C64("=f", d) : "l"(da), "l"(db), "n"(TB));
}
__device__ __forceinline__ void mma_rs(float (&d)[64], const uint32_t* a, uint64_t db, int acc) {
    asm volatile("{\n.reg .pred p;\nsetp.ne.b32 p, %69, 0;\n"
                 "wgmma.mma_async.sync.aligned.m64n128k16.f32.bf16.bf16 " ACC64 ", {%64, %65, %66, %67}, %68, p, 1, 1, 1;\n}"
                 : C64("+f", d) : "r"(a[0]), "r"(a[1]), "r"(a[2]), "r"(a[3]), "l"(db), "r"(acc));
}

__device__ __forceinline__ void stage_tile(const float (&d)[64], float s0, float s1, uint32_t st_addr) {
#pragma unroll
    for (int j = 0; j < 8; j++)
        stsm4((st_addr + (j >> 2) * A_SLOT) ^ ((j & 3) * 32),
              pack_bf16(d[8 * j] * s0, d[8 * j + 1] * s0), pack_bf16(d[8 * j + 2] * s1, d[8 * j + 3] * s1),
              pack_bf16(d[8 * j + 4] * s0, d[8 * j + 5] * s0), pack_bf16(d[8 * j + 6] * s1, d[8 * j + 7] * s1));
}
__device__ __forceinline__ void stage_tile(const float (&d)[64], uint32_t st_addr) {
#pragma unroll
    for (int j = 0; j < 8; j++)
        stsm4((st_addr + (j >> 2) * A_SLOT) ^ ((j & 3) * 32), pack_bf16(d[8 * j], d[8 * j + 1]), pack_bf16(d[8 * j + 2], d[8 * j + 3]),
              pack_bf16(d[8 * j + 4], d[8 * j + 5]), pack_bf16(d[8 * j + 6], d[8 * j + 7]));
}
__device__ __forceinline__ void stage_packed(const uint32_t (&p)[32], uint32_t st_addr) {
#pragma unroll
    for (int j = 0; j < 8; j++) stsm4((st_addr + (j >> 2) * A_SLOT) ^ ((j & 3) * 32), p[4 * j], p[4 * j + 1], p[4 * j + 2], p[4 * j + 3]);
}
__device__ __forceinline__ void stash_tile(const float (&d)[64], char* dst) {
#pragma unroll
    for (int j = 0; j < 8; j++)
        *(uint4*)(dst + (j >> 2) * A_SLOT + (j & 3) * 512) =
            make_uint4(pack_bf16(d[8 * j], d[8 * j + 1]), pack_bf16(d[8 * j + 2], d[8 * j + 3]),
                       pack_bf16(d[8 * j + 4], d[8 * j + 5]), pack_bf16(d[8 * j + 6], d[8 * j + 7]));
}
__device__ __forceinline__ void stash_packed(const uint32_t (&p)[32], char* dst) {
#pragma unroll
    for (int j = 0; j < 8; j++)
        *(uint4*)(dst + (j >> 2) * A_SLOT + (j & 3) * 512) = make_uint4(p[4 * j], p[4 * j + 1], p[4 * j + 2], p[4 * j + 3]);
}
__device__ __forceinline__ void write_out(const float (&d)[64], uint32_t st_addr, uint32_t rows, char* out, uint32_t op, int warp, int lane) {
    stage_tile(d, st_addr);
    __syncwarp();
    char* dst = out + ((op_g(op) & 7) * SQ + warp * 16) * (4 * DM) + (op_g(op) >> 3) * (2 * DM) + (op_h(op) & 3) * 512 + (op_takeover(op) ? 0 : 256);
#pragma unroll
    for (int j = 0; j < 8; j++) {
        const int r = (j & 3) * 4 + (lane >> 3);
        uint4 v;
        asm volatile("ld.shared.v4.u32 {%0, %1, %2, %3}, [%4];" : "=r"(v.x), "=r"(v.y), "=r"(v.z), "=r"(v.w)
                     : "r"(rows + (j >> 2) * A_SLOT + r * 128 + (((lane ^ r) & 7) << 4)) : "memory");
        *(uint4*)(dst + r * (4 * DM) + (j >> 2) * 128 + (lane & 7) * 16) = v;
    }
}
__device__ __forceinline__ void publish_tile(uint32_t bar, int lane) {
    asm volatile("fence.proxy.async.shared::cta;" ::: "memory");
    __syncwarp();
    if (lane == 0) mbar_arrive(bar);
}

template <bool INIT>
__device__ __forceinline__ void gemm_step(float (&c)[64], uint64_t a, uint64_t b) {
    if (INIT) mma_ss_init<1>(c, a, b); else mma_ss<1>(c, a, b);
#pragma unroll
    for (int kk = 1; kk < 4; kk++) mma_ss<1>(c, a + DOFF(kk * 32), b + DOFF(kk * 2048));
}

template <bool INIT>
__device__ __forceinline__ void gemm_phase1(float (&c0)[64], uint32_t sb, int wg, int lane, uint32_t& it, int nk) {
    const uint64_t a0 = mk_desc(sb + OFF_A + wg * 8192, 16), b0 = mk_desc(sb + OFF_B, 8192);
    if (INIT) {
        mbar_wait(sb + BAR_FULL, 0);
        wg_fence();
        gemm_step<true>(c0, a0, b0);
        wg_commit();
        wg_wait<0>();
        if (lane == 0) mbar_arrive(sb + BAR_EMPTY);
        it++;
    }
#pragma unroll 1
    for (int ks = INIT; ks < nk; ks++) {
        const uint32_t s = it & 3;
        mbar_wait(sb + BAR_FULL + s * 8, (it >> 2) & 1);
        wg_fence();
        gemm_step<false>(c0, a0 + s * (A_SLOT >> 4), b0 + s * (B_SLOT >> 4));
        wg_commit();
        wg_wait<0>();
        if (lane == 0) mbar_arrive(sb + BAR_EMPTY + s * 8);
        it++;
    }
    reg_fence(c0);
}

__device__ __forceinline__ void gemm_phase2(float (&c0)[64], float (&c1)[64], const uint32_t (&p)[32], uint32_t sb, int wg, int lane,
                                            uint32_t& it, int nk, uint32_t pend, uint32_t op, uint32_t staged) {
    const uint64_t a0 = mk_desc(sb + OFF_A + wg * 8192, 16), b0 = mk_desc(sb + OFF_B, 8192);
    char* const stash = (char*)g_o + (threadIdx.x >> 5) * 2048 + lane * 16;
    const uint32_t ph0 = (it >> 2) & 1;
    mbar_wait(sb + BAR_FULL, ph0);
    wg_fence();
    gemm_step<true>(c0, a0, b0);
    wg_commit();
    mbar_wait(sb + BAR_FULL + 8, ph0);
    wg_fence();
    gemm_step<false>(c0, a0 + DOFF(A_SLOT), b0 + DOFF(B_SLOT));
    wg_commit();
    if (pend) {
        stash_packed(p, stash + (size_t)pend * 2 * A_SLOT);
        __syncwarp();
        if (lane == 0) mbar_arrive(staged);
    }
    wg_fence();
    gemm_step<true>(c1, a0, b0 + DOFF(16384));
    wg_commit();
    gemm_step<false>(c1, a0 + DOFF(A_SLOT), b0 + DOFF(B_SLOT + 16384));
    wg_commit();
    wg_wait<1>();
    if (lane == 0) mbar_arrive(sb + BAR_EMPTY);
    wg_wait<0>();
    if (lane == 0) mbar_arrive(sb + BAR_EMPTY + 8);
    it += 2;
#pragma unroll 1
    for (int ks = 2; ks < nk - 2; ks++) {
        const uint32_t s = it & 3;
        const uint64_t a = a0 + s * (A_SLOT >> 4), b = b0 + s * (B_SLOT >> 4);
        mbar_wait(sb + BAR_FULL + s * 8, (it >> 2) & 1);
        wg_fence();
#pragma unroll
        for (int kk = 0; kk < 4; kk++) {
            mma_ss<1>(c0, a + DOFF(kk * 32), b + DOFF(kk * 2048));
            mma_ss<1>(c1, a + DOFF(kk * 32), b + DOFF(16384 + kk * 2048));
        }
        wg_commit();
        wg_wait<0>();
        if (lane == 0) mbar_arrive(sb + BAR_EMPTY + s * 8);
        it++;
    }
    const uint32_t ph1 = (it >> 2) & 1, s1 = it & 2;
    const uint64_t a1 = a0 + s1 * (A_SLOT >> 4), b1 = b0 + s1 * (B_SLOT >> 4);
    mbar_wait(sb + BAR_FULL + s1 * 8, ph1);
    wg_fence();
    gemm_step<false>(c0, a1, b1);
    wg_commit();
    mbar_wait(sb + BAR_FULL + s1 * 8 + 8, ph1);
    wg_fence();
    gemm_step<false>(c0, a1 + DOFF(A_SLOT), b1 + DOFF(B_SLOT));
    wg_commit();
    gemm_step<false>(c1, a1, b1 + DOFF(16384));
    gemm_step<false>(c1, a1 + DOFF(A_SLOT), b1 + DOFF(B_SLOT + 16384));
    wg_commit();
    wg_wait<1>();
    reg_fence(c0);
    if (op_type(op) == OP_OT) {
        float4* dst = g_park + op_tile(op) * (12 * 16 * 32) + (threadIdx.x >> 5) * (16 * 32) + lane;
#pragma unroll
        for (int j = 0; j < 16; j++) dst[j * 32] = make_float4(c0[4 * j], c0[4 * j + 1], c0[4 * j + 2], c0[4 * j + 3]);
        __syncwarp();
        if (lane == 0) mbar_arrive(staged);
    } else if (op & Q_STASH) {
        stash_tile(c0, stash + (size_t)op_head(op) * 2 * A_SLOT);
    }
    wg_wait<0>();
    reg_fence(c1);
    if (lane == 0) { mbar_arrive(sb + BAR_EMPTY + s1 * 8); mbar_arrive(sb + BAR_EMPTY + s1 * 8 + 8); }
    it += 2;
}

__device__ __forceinline__ void qk_issue(float (&s)[64], uint64_t qa, uint64_t kb) {
    mma_ss_init<0>(s, qa, kb);
#pragma unroll
    for (int kk = 1; kk < 8; kk++)
        mma_ss<0>(s, qa + DOFF((kk >> 2) * A_SLOT + (kk & 3) * 32), kb + DOFF((kk >> 2) * 16384 + (kk & 3) * 32));
}

__device__ __forceinline__ int imax3(float a, float b, float c) {
    return __vimax3_s32(__float_as_int(a), __float_as_int(b), __float_as_int(c));
}

__device__ __forceinline__ void softmax_block(float (&s)[64], uint32_t (&p)[32], float (&o)[64], float& n0, float& n1,
                                              float& l0, float& l1, int never, bool first) {
    constexpr float C = 0.08838834764831845f * 1.4426950408889634f;
    int i0 = imax3(s[0], s[1], s[4]), i1 = imax3(s[2], s[3], s[6]);
    int j0 = imax3(s[5], s[8], s[9]), j1 = imax3(s[7], s[10], s[11]);
#pragma unroll
    for (int j = 3; j < 15; j += 2) {
        i0 = imax3(__int_as_float(i0), s[4 * j], s[4 * j + 1]);
        i1 = imax3(__int_as_float(i1), s[4 * j + 2], s[4 * j + 3]);
        j0 = imax3(__int_as_float(j0), s[4 * j + 4], s[4 * j + 5]);
        j1 = imax3(__int_as_float(j1), s[4 * j + 6], s[4 * j + 7]);
    }
    i0 = imax3(__int_as_float(i0), s[60], s[61]);
    i1 = imax3(__int_as_float(i1), s[62], s[63]);
    i0 = imax3(__int_as_float(i0), __int_as_float(j0), 0.f);
    i1 = imax3(__int_as_float(i1), __int_as_float(j1), 0.f);
    if (__any_sync(0xffffffffu, !(fmaf(__int_as_float(i0), C, n0) <= 8.f && fmaf(__int_as_float(i1), C, n1) <= 8.f))) {
        i0 = max(i0, __shfl_xor_sync(0xffffffffu, i0, 1));
        i1 = max(i1, __shfl_xor_sync(0xffffffffu, i1, 1));
        i0 = max(i0, __shfl_xor_sync(0xffffffffu, i0, 2));
        i1 = max(i1, __shfl_xor_sync(0xffffffffu, i1, 2));
        float x0 = __int_as_float(i0), x1 = __int_as_float(i1);
        if (__any_sync(0xffffffffu, i0 == 0 || i1 == 0)) {
            x0 = x1 = -INFINITY;
#pragma unroll
            for (int j = 0; j < 16; j++) {
                x0 = fmaxf(x0, fmaxf(s[4 * j], s[4 * j + 1]));
                x1 = fmaxf(x1, fmaxf(s[4 * j + 2], s[4 * j + 3]));
            }
            x0 = fmaxf(x0, __shfl_xor_sync(0xffffffffu, x0, 1));
            x1 = fmaxf(x1, __shfl_xor_sync(0xffffffffu, x1, 1));
            x0 = fmaxf(x0, __shfl_xor_sync(0xffffffffu, x0, 2));
            x1 = fmaxf(x1, __shfl_xor_sync(0xffffffffu, x1, 2));
        }
        x0 = fminf(n0, -x0 * C);
        x1 = fminf(n1, -x1 * C);
        if (!first) {
            const float r0 = ex2(x0 - n0), r1 = ex2(x1 - n1);
            l0 *= r0;
            l1 *= r1;
#pragma unroll
            for (int j = 0; j < 32; j++) { o[2 * j] *= (j & 1) ? r1 : r0; o[2 * j + 1] *= (j & 1) ? r1 : r0; }
        }
        n0 = x0;
        n1 = x1;
    }
    float t0 = l0, t1 = l1, u0 = 0.f, u1 = 0.f;
    constexpr int LAG = 2;
#pragma unroll
    for (int c = -1; c < 32 + LAG; c++) {
        if (c >= 0 && c < 32) { s[2 * c] = ex2(s[2 * c]); s[2 * c + 1] = ex2(s[2 * c + 1]); }
        if (c + 1 < 32) {
            const int j = c + 1;
            s[2 * j] = fmaf(s[2 * j], C, (j & 1) ? n1 : n0);
            s[2 * j + 1] = fmaf(s[2 * j + 1], C, (j & 1) ? n1 : n0);
        }
        if (c >= LAG) {
            const int j = c - LAG;
            if (j & 1) { t1 += s[2 * j]; if (j == 1) u1 = s[3]; else u1 += s[2 * j + 1]; }
            else { t0 += s[2 * j]; if (j == 0) u0 = s[1]; else u0 += s[2 * j + 1]; }
            p[j] = pack_bf16(s[2 * j], s[2 * j + 1]);
        }
        if (c >= 0 && c < 31) {
#pragma unroll
            for (int i = 0; i < 64; i++) if (i >= 2 * (c - LAG + 1)) asm volatile("" : "+f"(s[i]));
#pragma unroll
            for (int i = 0; i < 32; i++) if (i < c - LAG + 1) asm volatile("" : "+r"(p[i]));
            asm volatile("" : "+f"(t0), "+f"(t1), "+f"(u0), "+f"(u1));
            SCHED_FENCE(never);
        }
    }
    l0 = t0 + u0;
    l1 = t1 + u1;
}

__device__ __forceinline__ void attn_epilogue(float (&o)[64], float l0, float l1, uint32_t st_addr, uint32_t staged, int lane) {
    l0 += __shfl_xor_sync(0xffffffffu, l0, 1);
    l1 += __shfl_xor_sync(0xffffffffu, l1, 1);
    l0 += __shfl_xor_sync(0xffffffffu, l0, 2);
    l1 += __shfl_xor_sync(0xffffffffu, l1, 2);
    stage_tile(o, __fdividef(1.f, l0), __fdividef(1.f, l1), st_addr);
    publish_tile(staged, lane);
}

__global__ void __launch_bounds__(NTHREADS, 1) mha2_kernel(const __grid_constant__ Params prm) {
    extern __shared__ __align__(1024) char smem_raw[];
    const uint32_t sb = smem_u32(smem_raw);
    const int tid = threadIdx.x, lane = tid & 31;
    const int warp = __shfl_sync(0xffffffffu, tid >> 5, 0);
    const int cta = blockIdx.x;
    const uint16_t* ops = prm.ops[cta];

    if (warp == 12 && elect_one()) {
        for (int i = 0; i < 4; i++) mbar_init(sb + BAR_FULL + 8 * i, 1);
        asm volatile("fence.mbarrier_init.release.cluster;" ::: "memory");
        const uint32_t op = ops[0], br = op_g(op) >> 3;
        const bool two = op & Q_TWO;
#pragma unroll 1
        for (int s = 0; s < 4; s++) {
            mbar_expect_tx(sb + BAR_FULL + s * 8, two ? A_SLOT + B_SLOT : A_SLOT + B_SLOT / 2);
            tma_2d(sb + OFF_A + s * A_SLOT, &prm.x[br], s * 64, (op_g(op) & 7) * SQ, sb + BAR_FULL + s * 8);
            tma_3d(sb + OFF_B + s * B_SLOT, &prm.wq[br], 0, s * 64, op_h(op) * 2, sb + BAR_FULL + s * 8);
            if (two) tma_3d(sb + OFF_B + s * B_SLOT + 16384, &prm.wq[br], 0, s * 64, op_h(op) * 2 + 2, sb + BAR_FULL + s * 8);
        }
        asm volatile("prefetch.tensormap [%0];" ::"l"(&prm.k[br]) : "memory");
        asm volatile("prefetch.tensormap [%0];" ::"l"(&prm.v[br]) : "memory");
    }
    if (tid == 0) {
        for (int i = 0; i < 4; i++) mbar_init(sb + BAR_EMPTY + 8 * i, 12);
        for (int i = 0; i < 2; i++) mbar_init(sb + BAR_QFREE + 8 * i, 3);
        for (int i = 0; i < 3; i++) {
            mbar_init(sb + BAR_STAGED + 8 * i, 4);
            mbar_init(sb + BAR_QREADY + 8 * i, 1);
            mbar_init(sb + BAR_QLOAD + 8 * i, 1);
        }
        asm volatile("fence.mbarrier_init.release.cluster;" ::: "memory");
    }
    __syncthreads();

    if (warp >= 12) {
        asm volatile("setmaxnreg.dec.sync.aligned.u32 32;");
        const unsigned epoch0 = g_epoch[cta];
        if (warp == 12) {
            uint32_t it = 4;
            bool after_att = false;
#pragma unroll 1
            for (int i = 0;; i++) {
                const uint32_t op = __shfl_sync(0xffffffffu, (uint32_t)ops[i], 0);
                const uint32_t ty = op_type(op), g = op_g(op), h = op_h(op), br = g >> 3;
                if (ty == OP_END) break;
                if (ty == OP_AT) {
                    const int row0 = ((g & 7) * NH + h) * SK;
#pragma unroll 1
                    for (int t = 0; t < 16; t++, it++) {
                        const uint32_t s = it & 3;
                        mbar_wait_sleep(sb + BAR_EMPTY + s * 8, ((it >> 2) & 1) ^ 1);
                        if (elect_one()) {
                            mbar_expect_tx(sb + BAR_FULL + s * 8, B_SLOT);
                            tma_3d_stream(sb + OFF_B + s * B_SLOT, (t & 1) ? &prm.v[br] : &prm.k[br], 0, row0 + (t >> 1) * 128, 0,
                                          sb + BAR_FULL + s * 8);
                        }
                    }
                    after_att = true;
                } else if (ty == OP_Q) {
                    const bool two = op & Q_TWO;
#pragma unroll 1
                    for (int ks = it & 15; ks < 16; ks++, it++) {
                        const uint32_t s = it & 3;
                        if (after_att && (ks == 0 || ks == 2)) mbar_wait_sleep(sb + BAR_QFREE + ks * 4, 0);
                        mbar_wait_sleep(sb + BAR_EMPTY + s * 8, ((it >> 2) & 1) ^ 1);
                        if (elect_one()) {
                            mbar_expect_tx(sb + BAR_FULL + s * 8, two ? A_SLOT + B_SLOT : A_SLOT + B_SLOT / 2);
                            tma_2d(sb + OFF_A + s * A_SLOT, &prm.x[br], ks * 64, (g & 7) * SQ, sb + BAR_FULL + s * 8);
                            tma_3d(sb + OFF_B + s * B_SLOT, &prm.wq[br], 0, ks * 64, h * 2, sb + BAR_FULL + s * 8);
                            if (two) tma_3d(sb + OFF_B + s * B_SLOT + 16384, &prm.wq[br], 0, ks * 64, h * 2 + 2, sb + BAR_FULL + s * 8);
                        }
                    }
                    after_att = false;
                } else {
                    unsigned epoch3;
                    asm volatile("mad.lo.u32 %0, %1, 3, 3;" : "=r"(epoch3) : "r"(epoch0));
                    const char* osrc = (const char*)g_o + (size_t)g * NH * 2 * A_SLOT;
                    const int k1 = op_k1(op), k0 = op_takeover(op) ? k1 : 0, col = (h & 3) * 4;
                    const bool own = k0 >= 48;
                    uint32_t todo = own ? (~0u << (k0 >> 1)) & ~(0x10000000u << (h & 3)) : 0xF0000000u, ready = 0, hk = 28 + (h & 3);
#pragma unroll 1
                    for (int ks = k0; ks < 64; ks++, it++) {
                        const uint32_t s = it & 3;
                        const bool have_a = own && ks < k0 + 2;
                        if (k0 && ks == 60) flag_wait(g_pflag + op_tile(op), epoch3);
                        if ((ks & 1) == 0 && !have_a) {
                            const uint32_t want = (own || ks >= 56) ? todo : 1u << (ks >> 1);
                            if (!(ready & want)) {
                                ready = flag_wait_any(g_flag + g * NH + lane, epoch3, want);
                                __syncwarp();
                                asm volatile("fence.proxy.async.global;" ::: "memory");
                            }
                            hk = __ffs(ready & want) - 1;
                            todo &= ~(1u << hk);
                        }
                        __syncwarp();
                        if (after_att && ks == k0 + (own ? 4 : 0)) mbar_wait_sleep(sb + BAR_QFREE, 0);
                        if (after_att && ks == k0 + 2) mbar_wait_sleep(sb + BAR_QFREE + 8, 0);
                        mbar_wait_sleep(sb + BAR_EMPTY + s * 8, ((it >> 2) & 1) ^ 1);
                        const int kk = hk * 2 + (ks & 1);
                        if (elect_one()) {
                            mbar_expect_tx(sb + BAR_FULL + s * 8, (have_a ? 0 : A_SLOT) + (ks < k1 ? B_SLOT : B_SLOT / 2));
                            if (!have_a) bulk_load(sb + OFF_A + s * A_SLOT, osrc + (size_t)kk * A_SLOT, A_SLOT, sb + BAR_FULL + s * 8);
                            tma_3d(sb + OFF_B + s * B_SLOT, &prm.wo[br], 0, kk * 64, (ks < k1 || k0) ? col : col + 2, sb + BAR_FULL + s * 8);
                            if (ks < k1) tma_3d(sb + OFF_B + s * B_SLOT + 16384, &prm.wo[br], 0, kk * 64, col + 2, sb + BAR_FULL + s * 8);
                            if (ks >= 40 && ks < 56 && !k0) tma_prefetch_3d(&prm.wo[br], 0, (36 + (ks >> 1)) * 64, col + (ks & 1) * 2);
                        }
                    }
                }
            }
        } else {
            const int w = warp - 13;
            const unsigned epoch = epoch0 + 1;
            uint32_t nq = 0;
#pragma unroll 1
            for (int i = 0;; i++) {
                const uint32_t op = __shfl_sync(0xffffffffu, (uint32_t)ops[i], 0);
                const uint32_t ty = op_type(op);
                if (ty == OP_END || (ty == OP_OT && op_takeover(op))) break;
                const uint32_t n1 = __shfl_sync(0xffffffffu, (uint32_t)ops[i + 1], 0);
                const bool more = op_type(n1) == OP_AT && !(n1 & AT_LAST);
                mbar_wait_sleep(sb + BAR_STAGED + w * 8, i & 1);
                if (lane == 0) {
                    if (ty == OP_Q) {
                        if (op & Q_STASH) {
                            __threadfence();
                            asm volatile("st.relaxed.gpu.global.u32 [%0], %1;" ::"l"(g_qflag + op_head(op) * 4 + w), "r"(epoch) : "memory");
                            asm volatile("st.relaxed.gpu.global.u32 [%0], %1;" ::"l"(g_qflag + op_head(op) * 4 + 4 + w), "r"(epoch) : "memory");
                        }
                    } else if (ty == OP_AT) {
                        char* dst = (char*)g_o + (size_t)op_head(op) * 2 * A_SLOT + w * 8192;
                        const uint32_t src = sb + OFF_A + ((op & AT_BUF1) ? 2 * A_SLOT : 0) + w * 8192;
                        bulk_store_stream(dst, src, 8192);
                        bulk_store_stream(dst + A_SLOT, src + A_SLOT, 8192);
                        asm volatile("cp.async.bulk.commit_group;" ::: "memory");
                        asm volatile("cp.async.bulk.wait_group 0;" ::: "memory");
                        if (!more) mbar_arrive(sb + BAR_QFREE + ((op & AT_BUF1) ? 8 : 0));
                        asm volatile("red.release.gpu.global.add.u32 [%0], 1;" ::"l"(g_flag + op_head(op)) : "memory");
                    } else {
                        asm volatile("red.release.gpu.global.add.u32 [%0], 1;" ::"l"(g_pflag + op_tile(op)) : "memory");
                    }
                }
                __syncwarp();
                if (!more) continue;
                const uint32_t n2 = __shfl_sync(0xffffffffu, (uint32_t)ops[i + 2], 0);
                if (!(n2 & AT_STASH)) continue;
                const uint32_t buf = sb + OFF_A + ((n2 & AT_BUF1) ? 2 * A_SLOT : 0) + w * 8192;
                if (lane == 0) {
                    flag_wait(g_qflag + op_head(n2) * 4 + w, epoch);
                    asm volatile("fence.proxy.async;" ::: "memory");
                    const char* src = (const char*)g_o + (size_t)op_head(n2) * 2 * A_SLOT + w * 8192;
                    mbar_expect_tx(sb + BAR_QLOAD + w * 8, 16384);
                    bulk_load_stream(buf, src, 8192, sb + BAR_QLOAD + w * 8);
                    bulk_load_stream(buf + A_SLOT, src + A_SLOT, 8192, sb + BAR_QLOAD + w * 8);
                }
                __syncwarp();
                mbar_wait_sleep(sb + BAR_QLOAD + w * 8, nq);
                nq ^= 1;
#pragma unroll 1
                for (int c = 0; c < 8; c++) {
                    const uint32_t blk = buf + (c >> 2) * A_SLOT + (c & 3) * 2048;
                    uint32_t v[16];
#pragma unroll
                    for (int j = 0; j < 4; j++)
                        asm volatile("ld.shared.v4.u32 {%0, %1, %2, %3}, [%4];"
                                     : "=r"(v[4 * j]), "=r"(v[4 * j + 1]), "=r"(v[4 * j + 2]), "=r"(v[4 * j + 3])
                                     : "r"(blk + lane * 16 + j * 512) : "memory");
                    __syncwarp();
                    const uint32_t st = blk + (lane & 15) * 128 + (((lane >> 4) ^ (lane & 7)) << 4);
#pragma unroll
                    for (int j = 0; j < 4; j++) stsm4(st ^ (j * 32), v[4 * j], v[4 * j + 1], v[4 * j + 2], v[4 * j + 3]);
                }
                publish_tile(sb + BAR_QREADY + w * 8, lane);
            }
        }
        asm volatile("bar.sync 4, 128;" ::: "memory");
        if (tid == 384) g_epoch[cta] = epoch0 + 1;

    } else {
        asm volatile("setmaxnreg.inc.sync.aligned.u32 160;");
        const int wg = warp >> 2;
        const int my_bar = 1 + wg, next_bar = wg == 2 ? 1 : 2 + wg;
        const uint32_t qa0 = sb + OFF_A + wg * 8192;
        const uint32_t st_addr = qa0 + ((warp & 3) * 16 + (lane & 15)) * 128 + (((lane >> 4) ^ (lane & 7)) << 4);
        const uint32_t staged = sb + BAR_STAGED + wg * 8;
        const uint64_t qd0 = mk_desc(qa0, 16), kd0 = mk_desc(sb + OFF_B, 16), vd0 = mk_desc(sb + OFF_B, 16384);
        float o[64], s[64];
        uint32_t p[32];
        uint32_t it = 0, pend = 0;
        int i = 0;
#pragma unroll
        for (int j = 0; j < 32; j++) p[j] = 0;
        TSTAMP(0);
#pragma unroll 1
        for (;;) {
            const uint32_t op = __shfl_sync(0xffffffffu, (uint32_t)ops[i], 0);
            if (op_type(op) == OP_END) break;
            if (op_type(op) != OP_AT) {
                if (op_type(op) == OP_Q && !(op & Q_TWO)) {
                    gemm_phase1<true>(o, sb, wg, lane, it, 16);
                    stage_tile(o, st_addr);
                    publish_tile(staged, lane);
                } else if (op_type(op) == OP_OT && op_takeover(op)) {
#pragma unroll
                    for (int j = 0; j < 64; j++) s[j] = 0.f;
                    reg_fence(s);
                    asm volatile("bar.sync %0, 128;" ::"r"(5 + wg) : "memory");
                    gemm_phase1<false>(s, sb, wg, lane, it, 60 - op_k1(op));
                    const float4* src = g_park + op_tile(op) * (12 * 16 * 32) + (tid >> 5) * (16 * 32) + lane;
                    const uint64_t b0 = mk_desc(sb + OFF_B, 8192);
#pragma unroll
                    for (int ks = 0; ks < 4; ks++) {
                        const uint32_t sl = it & 3;
                        mbar_wait(sb + BAR_FULL + sl * 8, (it >> 2) & 1);
                        wg_fence();
                        gemm_step<false>(s, qd0 + sl * (A_SLOT >> 4), b0 + sl * (B_SLOT >> 4));
                        wg_commit();
                        it++;
#pragma unroll
                        for (int j = 4 * ks; j < 4 * ks + 4; j++) {
                            const float4 v = __ldcg(src + j * 32);
                            o[4 * j] = v.x; o[4 * j + 1] = v.y; o[4 * j + 2] = v.z; o[4 * j + 3] = v.w;
                        }
                    }
                    wg_wait<0>();
                    reg_fence(s);
#pragma unroll
                    for (int j = 0; j < 64; j++) s[j] += o[j];
                    write_out(s, st_addr, sb + OFF_A + warp * 2048, prm.out, op, warp, lane);
                    TSTAMP(i + 1);
                    break;
                } else {
                    gemm_phase2(o, s, p, sb, wg, lane, it, op_type(op) == OP_Q ? 16 : op_k1(op), pend, op, staged);
                    if (op_type(op) == OP_OT) {
                        TSTAMP(15);
                        gemm_phase1<false>(s, sb, wg, lane, it, 64 - op_k1(op));
                        write_out(s, st_addr, sb + OFF_A + warp * 2048, prm.out, op, warp, lane);
                        TSTAMP(i + 1);
                        break;
                    }
#pragma unroll
                    for (int j = 0; j < 32; j++) p[j] = pack_bf16(s[2 * j], s[2 * j + 1]);
                    pend = 0;
                    if (op & Q_STASH) {
                        pend = op_head(op) + 1;
                    } else {
                        stage_tile(o, st_addr);
                        stage_packed(p, st_addr + 2 * A_SLOT);
                        publish_tile(staged, lane);
                    }
                }
                i++;
                TSTAMP(i);
                continue;
            }
            float n0 = INFINITY, n1 = INFINITY, l0 = 0.f, l1 = 0.f;
            int t = 0, tend = 8 | ((ops[i + 1] & AT_STASH) ? 8 << 8 : 16 << 8);
            while (!(ops[i++] & AT_LAST)) tend += 8;
            tend = __shfl_sync(0xffffffffu, tend, 0);
            if (wg == 2) bar_arrive(1);
            mbar_wait(sb + BAR_FULL, (it >> 2) & 1);
            bar_sync(my_bar);
            wg_fence();
            qk_issue(s, qd0, kd0);
            wg_commit();
            bar_arrive(next_bar);
            wg_wait<0>();
            reg_fence(s);
            if (lane == 0) mbar_arrive(sb + BAR_EMPTY);
            it++;
            softmax_block(s, p, o, n0, n1, l0, l1, prm.never, true);
#pragma unroll 1
            for (t++; t != (tend & 255); t++) {
                const bool flip = (t & 7) == 0;
                if (flip && t >= (tend >> 8)) mbar_wait(sb + BAR_QREADY + wg * 8, ((t - (tend >> 8)) >> 3) & 1);
                const uint32_t sv = it & 3, sk = (it + 1) & 3;
                const uint64_t vb = vd0 + sv * (B_SLOT >> 4), kb = kd0 + sk * (B_SLOT >> 4), qd = qd0 + (t & 8) * (2 * A_SLOT / 128);
                mbar_wait(sb + BAR_FULL + sv * 8, (it >> 2) & 1);
                bar_sync(my_bar);
                wg_fence();
                mma_rs(o, p, vb, (t & 7) != 1);
#pragma unroll
                for (int kk = 1; kk < 7; kk++) mma_rs(o, p + 4 * kk, vb + DOFF(kk * 2048), 1);
                wg_commit();
                mma_rs(o, p + 28, vb + DOFF(7 * 2048), 1);
                wg_commit();
                mbar_wait(sb + BAR_FULL + sk * 8, ((it + 1) >> 2) & 1);
                wg_wait<1>();
                wg_fence();
                qk_issue(s, qd, kb);
                wg_commit();
                bar_arrive(next_bar);
                wg_wait<1>();
                reg_fence(o);
                if (lane == 0) mbar_arrive(sb + BAR_EMPTY + sv * 8);
                if (flip) {
                    attn_epilogue(o, l0, l1, st_addr + (~t & 8) * (2 * A_SLOT / 8), staged, lane);
                    n0 = n1 = INFINITY;
                    l0 = l1 = 0.f;
                    TSTAMP(i - (((tend & 255) - t) >> 3));
                }
                wg_wait<0>();
                reg_fence(s);
                if (lane == 0) mbar_arrive(sb + BAR_EMPTY + sk * 8);
                it += 2;
                softmax_block(s, p, o, n0, n1, l0, l1, prm.never, flip);
            }
            {
                const uint64_t vb = vd0 + DOFF(3 * B_SLOT);
                mbar_wait(sb + BAR_FULL + 3 * 8, (it >> 2) & 1);
                bar_sync(my_bar);
                wg_fence();
#pragma unroll
                for (int kk = 0; kk < 8; kk++) mma_rs(o, p + 4 * kk, vb + DOFF(kk * 2048), 1);
                wg_commit();
                if (wg != 2) bar_arrive(next_bar);
                wg_wait<0>();
                reg_fence(o);
                if (lane == 0) mbar_arrive(sb + BAR_EMPTY + 3 * 8);
                it++;
                attn_epilogue(o, l0, l1, st_addr + (~t & 8) * (2 * A_SLOT / 8), staged, lane);
                TSTAMP(i);
            }
        }
    }
}

void build_schedule(uint16_t (*ops)[MAXOPS]) {
    for (int c = 0; c < NCTA; c++) for (int j = 0; j < MAXOPS; j++) ops[c][j] = OP_END;
    auto mk = [](uint32_t ty, int g, int h, uint32_t fl) { return (uint16_t)(ty | (g << 2) | (h << 6) | fl); };
    auto ncta = [](int g, int j) { return g * 8 + (j & 1) + (j >> 1) * 4; };
    auto mcta = [](int g, int j) { return g * 8 + 2 + (j & 1) + (j >> 1) * 4; };
    for (int g = 0; g < 16; g++) {
        const int q = g & 3;
        uint16_t* oe = ops[128 + (g >> 2)];
        int hn[7][4], hx[2] = {0, 0};
        int h = 6;
        const int pos0 = q == 0 ? 1 : q == 1 ? 2 : q == 2 ? 4 : 3, pos1 = q == 0 ? 1 : q == 1 ? 3 : q == 2 ? 6 : 3;
        for (int w = 1; w < 7; w++) {
            if (pos0 == w) hx[0] = h++;
            if (pos1 == w) hx[1] = h++;
            for (int j = 0; j < 4; j++) hn[w][j] = h++;
        }
        for (int j = 0; j < 4; j++) {
            uint16_t* o = ops[ncta(g, j)];
            o[0] = mk(OP_Q, g, j, 0);
            o[1] = mk(OP_AT, g, j, 0);
            for (int w = 1; w < 7; w++) o[w + 1] = mk(OP_AT, g, hn[w][j], AT_STASH | ((w & 1) ? AT_BUF1 : 0) | (w == 6 ? AT_LAST : 0));
            if (q != 3 || j != 1) {
                o[8] = mk(OP_OT, g, 4 | j, (K1N / 2) << 11);
                ops[mcta(g, j)][4] = mk(OP_OT, g, j, (K1N / 2) << 11);
            }
        }
        {
            uint16_t* o = ops[mcta(g, 0)];
            const int s0 = S0MODE == 0 ? (g & 1) : S0MODE == 1 ? 1 : (q != 0);
            o[s0] = mk(OP_Q, g, 4, Q_TWO);
            o[s0 + 1] = mk(OP_AT, g, 4, 0);
            o[s0 + 2] = mk(OP_AT, g, 5, AT_BUF1 | AT_LAST);
        }
        if (q == 0) oe[0] = mk(OP_Q, g, hx[0], Q_TWO);
        if (q < 3) {
            oe[2 * q + 1] = mk(OP_AT, g, hx[0], q ? AT_STASH : 0);
            oe[2 * q + 2] = mk(OP_AT, g, hx[1], (q ? AT_STASH : 0) | AT_BUF1 | (q == 2 ? AT_LAST : 0));
        } else {
            uint16_t* o = ops[mcta(g, 2)];
            o[0] = mk(OP_Q, g, hx[0], Q_TWO);
            o[1] = mk(OP_AT, g, hx[0], 0);
            o[2] = mk(OP_AT, g, hx[1], AT_BUF1 | AT_LAST);
            ops[mcta(g, 1)][5] = mk(OP_OT, g, 1, (K1E / 2) << 11);
            oe[7] = mk(OP_OT, g, 4 | 1, (K1E / 2) << 11);
        }
        int nq = 6;
        for (int sl = 0; sl < 5; sl++)
            for (int j = 0; j < 4; j++) {
                uint16_t* o = ops[mcta(g, j)];
                if (o[sl] == OP_END) {
                    if ((q == 0 || q == 3) && nq == hx[0]) nq += 2;
                    o[sl] = nq < 32 ? mk(OP_Q, g, nq, Q_TWO | Q_STASH) : mk(OP_Q, g + 3, 30, Q_TWO | Q_STASH);
                    nq += 2;
                }
            }
    }
}

typedef CUresult (*EncodeFn)(CUtensorMap*, CUtensorMapDataType, cuuint32_t, void*, const cuuint64_t*, const cuuint64_t*,
                             const cuuint32_t*, const cuuint32_t*, CUtensorMapInterleave, CUtensorMapSwizzle,
                             CUtensorMapL2promotion, CUtensorMapFloatOOBfill);

void encode(EncodeFn fn, CUtensorMap* m, void* ptr, int rank, const cuuint64_t* dims, const cuuint64_t* strides, const cuuint32_t* box,
            CUtensorMapL2promotion promo = CU_TENSOR_MAP_L2_PROMOTION_L2_128B) {
    const cuuint32_t es[3] = {1, 1, 1};
    fn(m, CU_TENSOR_MAP_DATA_TYPE_BFLOAT16, rank, ptr, dims, strides, box, es, CU_TENSOR_MAP_INTERLEAVE_NONE,
       CU_TENSOR_MAP_SWIZZLE_128B, promo, CU_TENSOR_MAP_FLOAT_OOB_FILL_NONE);
}

}

extern "C" void kernel_launch(void* const* d_in, const int* in_sizes, int n_in, void* d_out, int out_size) {
    static EncodeFn fn = nullptr;
    if (!fn) {
        cudaDriverEntryPointQueryResult qr;
        void* p = nullptr;
        cudaGetDriverEntryPoint("cuTensorMapEncodeTiled", &p, cudaEnableDefault, &qr);
        fn = (EncodeFn)p;
        cudaFuncSetAttribute(mha2_kernel, cudaFuncAttributeMaxDynamicSharedMemorySize, SMEM_BYTES);
    }
    Params prm;
    for (int br = 0; br < 2; br++) {
        void* x = d_in[5 * br + 0];
        void* k = d_in[5 * br + 1];
        void* v = d_in[5 * br + 2];
        void* wq = d_in[5 * br + 3];
        void* wo = d_in[5 * br + 4];
        {
            cuuint64_t dims[2] = {DM, NB * SQ}, st[1] = {DM * 2};
            cuuint32_t box[2] = {64, SQ};
            encode(fn, &prm.x[br], x, 2, dims, st, box);
        }
        {
            cuuint64_t dims[3] = {64, DM, NH * DH / 64}, st[2] = {NH * DH * 2, 128};
            cuuint32_t box[3] = {64, 64, 2};
            encode(fn, &prm.wq[br], wq, 3, dims, st, box);
        }
        {
            cuuint64_t dims[3] = {64, (cuuint64_t)NB * NH * SK, 2}, st[2] = {DH * 2, 128};
            cuuint32_t box[3] = {64, 128, 2};
            encode(fn, &prm.k[br], k, 3, dims, st, box, CU_TENSOR_MAP_L2_PROMOTION_NONE);
            encode(fn, &prm.v[br], v, 3, dims, st, box, CU_TENSOR_MAP_L2_PROMOTION_NONE);
        }
        {
            cuuint64_t dims[3] = {64, NH * DH, DM / 64}, st[2] = {DM * 2, 128};
            cuuint32_t box[3] = {64, 64, 2};
            encode(fn, &prm.wo[br], wo, 3, dims, st, box);
        }
    }
    prm.never = 0;
    prm.out = (char*)d_out;
    build_schedule(prm.ops);
    mha2_kernel<<<NCTA, NTHREADS, SMEM_BYTES>>>(prm);
}
```

```cpp
#include <cuda_runtime.h>
#include <cuda_bf16.h>
#include <cuda.h>
#include <stdint.h>

namespace {

constexpr int NB = 8, SQ = 192, DM = 1024, NH = 32, SK = 1024, DH = 128;
constexpr int NCTA = 132;
constexpr int MAXOPS = 10;
constexpr int NTHREADS = 512;
constexpr int K1N = 56;
constexpr int K1E = 34;
constexpr uint32_t STAG = 800;

constexpr uint32_t A_SLOT = 24576;
constexpr uint32_t B_SLOT = 32768;
constexpr uint32_t OFF_A = 0;
constexpr uint32_t OFF_B = 4 * A_SLOT;
constexpr uint32_t OFF_BAR = OFF_B + 4 * B_SLOT;
constexpr uint32_t BAR_FULL = OFF_BAR;
constexpr uint32_t BAR_EMPTY = OFF_BAR + 32;
constexpr uint32_t BAR_QFREE = OFF_BAR + 64;
constexpr uint32_t BAR_STAGED = OFF_BAR + 80;
constexpr uint32_t BAR_QREADY = OFF_BAR + 104;
constexpr uint32_t SMEM_BYTES = OFF_BAR + 128;

struct Params {
    CUtensorMap x[2], wq[2], k[2], v[2], wo[2];
    char* out;
    int never;
    uint16_t ops[NCTA][MAXOPS];
};

enum : uint32_t { OP_END = 0, OP_Q = 1, OP_AT = 2, OP_OT = 3 };
enum : uint32_t { Q_TWO = 1u << 11, Q_STASH = 1u << 12, Q_STASH1 = 1u << 13,
                  AT_STASH = 1u << 11, AT_BUF1 = 1u << 12, AT_LAST = 1u << 13 };
__host__ __device__ constexpr uint32_t op_type(uint32_t op) { return op & 3; }
__host__ __device__ constexpr uint32_t op_g(uint32_t op) { return (op >> 2) & 15; }
__host__ __device__ constexpr uint32_t op_h(uint32_t op) { return (op >> 6) & 31; }
__host__ __device__ constexpr uint32_t op_head(uint32_t op) { return op_g(op) * NH + op_h(op); }
__host__ __device__ constexpr uint32_t op_k1(uint32_t op) { return (op >> 11) * 2; }
__host__ __device__ constexpr bool op_takeover(uint32_t op) { return (op >> 8) & 1; }
__host__ __device__ constexpr uint32_t op_tile(uint32_t op) { return op_g(op) * 4 + ((op >> 6) & 3); }

__device__ __align__(1024) uint4 g_o[2 * NB * NH * 2 * (A_SLOT / 16)];
__device__ __align__(1024) float4 g_park[64 * 12 * 16 * 32];
__device__ unsigned g_flag[2 * NB * NH];
__device__ unsigned g_qflag[2 * NB * NH * 4];
__device__ unsigned g_pflag[64];
__device__ unsigned g_epoch[NCTA];

__device__ __forceinline__ uint32_t smem_u32(const void* p) { return (uint32_t)__cvta_generic_to_shared(p); }
__device__ __forceinline__ void mbar_init(uint32_t bar, uint32_t cnt) {
    asm volatile("mbarrier.init.shared::cta.b64 [%0], %1;" ::"r"(bar), "r"(cnt) : "memory");
}
__device__ __forceinline__ void mbar_expect_tx(uint32_t bar, uint32_t bytes) {
    asm volatile("mbarrier.arrive.expect_tx.shared::cta.b64 _, [%0], %1;" ::"r"(bar), "r"(bytes) : "memory");
}
__device__ __forceinline__ void mbar_arrive(uint32_t bar) {
    asm volatile("mbarrier.arrive.shared::cta.b64 _, [%0];" ::"r"(bar) : "memory");
}
__device__ __forceinline__ void mbar_wait(uint32_t bar, uint32_t parity) {
    asm volatile(
        "{\n.reg .pred p;\n.reg .u32 n;\nmov.u32 n, 0;\n"
        "LAB_WAIT:\n"
        "mbarrier.try_wait.parity.shared::cta.b64 p, [%0], %1;\n"
        "@p bra LAB_DONE;\n"
        "add.u32 n, n, 1;\nsetp.lt.u32 p, n, 0x2000000;\n@p bra LAB_WAIT;\ntrap;\n"
        "LAB_DONE:\n}" ::"r"(bar), "r"(parity) : "memory");
}
__device__ __forceinline__ void mbar_wait_sleep(uint32_t bar, uint32_t parity) {
    asm volatile(
        "{\n.reg .pred p;\n.reg .u32 n;\nmov.u32 n, 0;\n"
        "LAB_WAIT:\n"
        "mbarrier.try_wait.parity.shared::cta.b64 p, [%0], %1, 20000;\n"
        "@p bra LAB_DONE;\n"
        "add.u32 n, n, 1;\nsetp.lt.u32 p, n, 0x20000;\n@p bra LAB_WAIT;\ntrap;\n"
        "LAB_DONE:\n}" ::"r"(bar), "r"(parity) : "memory");
}
__device__ __forceinline__ void flag_wait(const unsigned* p, unsigned target) {
    asm volatile(
        "{\n.reg .pred p;\n.reg .u32 n, v;\n.reg .s32 d;\nmov.u32 n, 0;\n"
        "LAB_WAIT:\n"
        "ld.acquire.gpu.global.u32 v, [%0];\n"
        "sub.s32 d, v, %1;\nsetp.ge.s32 p, d, 0;\n"
        "@p bra LAB_DONE;\n"
        "nanosleep.u32 64;\n"
        "add.u32 n, n, 1;\nsetp.lt.u32 p, n, 0x400000;\n@p bra LAB_WAIT;\ntrap;\n"
        "LAB_DONE:\n}" ::"l"(p), "r"(target) : "memory");
}
__device__ __forceinline__ uint32_t flag_wait_any(const unsigned* p, unsigned target, uint32_t mask) {
    uint32_t r;
    asm volatile(
        "{\n.reg .pred p;\n.reg .u32 n, v;\n.reg .s32 d;\nmov.u32 n, 0;\n"
        "LAB_WAIT:\n"
        "ld.acquire.gpu.global.u32 v, [%1];\n"
        "sub.s32 d, v, %2;\nsetp.ge.s32 p, d, 0;\n"
        "vote.sync.ballot.b32 %0, p, 0xffffffff;\n"
        "and.b32 v, %0, %3;\nsetp.ne.u32 p, v, 0;\n"
        "@p bra LAB_DONE;\n"
        "nanosleep.u32 32;\n"
        "add.u32 n, n, 1;\nsetp.lt.u32 p, n, 0x400000;\n@p bra LAB_WAIT;\ntrap;\n"
        "LAB_DONE:\n}" : "=&r"(r) : "l"(p), "r"(target), "r"(mask) : "memory");
    return r;
}
__device__ __forceinline__ uint64_t policy_evict_first() {
    uint64_t r;
    asm("createpolicy.fractional.L2::evict_first.b64 %0, 1.0;" : "=l"(r));
    return r;
}
__device__ __forceinline__ void tma_2d(uint32_t dst, const CUtensorMap* m, int c0, int c1, uint32_t bar) {
    asm volatile("cp.async.bulk.tensor.2d.shared::cluster.global.mbarrier::complete_tx::bytes [%0], [%1, {%3, %4}], [%2];"
                 ::"r"(dst), "l"(m), "r"(bar), "r"(c0), "r"(c1) : "memory");
}
__device__ __forceinline__ void tma_w(uint32_t dst, const CUtensorMap* m, int k, int c, uint32_t bar) {
    asm volatile("cp.async.bulk.tensor.4d.shared::cluster.global.mbarrier::complete_tx::bytes [%0], [%1, {0, 0, %3, %4}], [%2];"
                 ::"r"(dst), "l"(m), "r"(bar), "r"(c), "r"(k >> 3) : "memory");
}
__device__ __forceinline__ void tma_4d_stream(uint32_t dst, const CUtensorMap* m, int c3, uint32_t bar) {
    asm volatile("cp.async.bulk.tensor.4d.shared::cluster.global.mbarrier::complete_tx::bytes.L2::cache_hint [%0], [%1, {0, 0, 0, %3}], [%2], %4;"
                 ::"r"(dst), "l"(m), "r"(bar), "r"(c3), "l"(policy_evict_first()) : "memory");
}
__device__ __forceinline__ void tma_prefetch_w(const CUtensorMap* m, int k, int c) {
    asm volatile("cp.async.bulk.prefetch.tensor.4d.L2.global [%0, {0, 0, %1, %2}];" ::"l"(m), "r"(c), "r"(k >> 3) : "memory");
}
__device__ __forceinline__ void bulk_load(uint32_t dst, const void* src, uint32_t bytes, uint32_t bar) {
    asm volatile("cp.async.bulk.shared::cluster.global.mbarrier::complete_tx::bytes [%0], [%1], %2, [%3];"
                 ::"r"(dst), "l"(src), "r"(bytes), "r"(bar) : "memory");
}
__device__ __forceinline__ void bulk_load_stream(uint32_t dst, const void* src, uint32_t bytes, uint32_t bar) {
    asm volatile("cp.async.bulk.shared::cluster.global.mbarrier::complete_tx::bytes.L2::cache_hint [%0], [%1], %2, [%3], %4;"
                 ::"r"(dst), "l"(src), "r"(bytes), "r"(bar), "l"(policy_evict_first()) : "memory");
}
__device__ __forceinline__ void bulk_store_stream(void* dst, uint32_t src, uint32_t bytes) {
    asm volatile("cp.async.bulk.global.shared::cta.bulk_group.L2::cache_hint [%0], [%1], %2, %3;"
                 ::"l"(dst), "r"(src), "r"(bytes), "l"(policy_evict_first()) : "memory");
}
__device__ __forceinline__ bool elect_one() {
    uint32_t r;
    asm volatile("{\n.reg .pred p;\nelect.sync _|p, 0xffffffff;\nselp.b32 %0, 1, 0, p;\n}" : "=r"(r));
    return r;
}
__device__ __forceinline__ void wg_fence() { asm volatile("wgmma.fence.sync.aligned;" ::: "memory"); }
__device__ __forceinline__ void wg_commit() { asm volatile("wgmma.commit_group.sync.aligned;" ::: "memory"); }
template <int N> __device__ __forceinline__ void wg_wait() { asm volatile("wgmma.wait_group.sync.aligned %0;" ::"n"(N) : "memory"); }
__device__ __forceinline__ void bar_sync(int id) { asm volatile("bar.sync %0, 256;" ::"r"(id) : "memory"); }
__device__ __forceinline__ void bar_arrive(int id) { asm volatile("bar.arrive %0, 256;" ::"r"(id) : "memory"); }
__device__ __forceinline__ float ex2(float x) { float y; asm("ex2.approx.ftz.f32 %0, %1;" : "=f"(y) : "f"(x)); return y; }
__device__ __forceinline__ uint32_t pack_bf16(float lo, float hi) {
    uint32_t r; asm("cvt.rn.bf16x2.f32 %0, %1, %2;" : "=r"(r) : "f"(hi), "f"(lo)); return r;
}
__device__ __forceinline__ void stsm4(uint32_t addr, uint32_t a, uint32_t b, uint32_t c, uint32_t d) {
    asm volatile("stmatrix.sync.aligned.m8n8.x4.shared.b16 [%0], {%1, %2, %3, %4};" ::"r"(addr), "r"(a), "r"(b), "r"(c), "r"(d) : "memory");
}
template <int N> __device__ __forceinline__ void reg_fence(float (&d)[N]) {
#pragma unroll
    for (int i = 0; i < N; i++) asm volatile("" : "+f"(d[i])::"memory");
}
#define SCHED_FENCE(x) asm volatile("{\n.reg .pred p;\nsetp.ne.s32 p, %0, 0;\n@p exit;\n}" ::"r"(x))

__device__ __forceinline__ uint64_t mk_desc(uint32_t addr, uint32_t lbo, uint32_t sbo = 1024) {
    uint32_t lo = ((addr & 0x3FFFF) >> 4) | ((lbo >> 4) << 16);
    return ((uint64_t)(0x40000000u | (sbo >> 4)) << 32) | lo;
}
#define DOFF(bytes) ((uint64_t)((bytes) >> 4))

#define ACC64 "{%0, %1, %2, %3, %4, %5, %6, %7, %8, %9, %10, %11, %12, %13, %14, %15, " \
              "%16, %17, %18, %19, %20, %21, %22, %23, %24, %25, %26, %27, %28, %29, %30, %31, " \
              "%32, %33, %34, %35, %36, %37, %38, %39, %40, %41, %42, %43, %44, %45, %46, %47, " \
              "%48, %49, %50, %51, %52, %53, %54, %55, %56, %57, %58, %59, %60, %61, %62, %63}"
#define C8(c, d, o) c(d[o]), c(d[o + 1]), c(d[o + 2]), c(d[o + 3]), c(d[o + 4]), c(d[o + 5]), c(d[o + 6]), c(d[o + 7])
#define C64(c, d) C8(c, d, 0), C8(c, d, 8), C8(c, d, 16), C8(c, d, 24), C8(c, d, 32), C8(c, d, 40), C8(c, d, 48), C8(c, d, 56)

template <int TB> __device__ __forceinline__ void mma_ss(float (&d)[64], uint64_t da, uint64_t db) {
    asm volatile("wgmma.mma_async.sync.aligned.m64n128k16.f32.bf16.bf16 " ACC64 ", %64, %65, 1, 1, 1, 0, %66;"
                 : C64("+f", d) : "l"(da), "l"(db), "n"(TB));
}
template <int TB> __device__ __forceinline__ void mma_ss_init(float (&d)[64], uint64_t da, uint64_t db) {
    asm volatile("wgmma.mma_async.sync.aligned.m64n128k16.f32.bf16.bf16 " ACC64 ", %64, %65, 0, 1, 1, 0, %66;"
                 : C64("=f", d) : "l"(da), "l"(db), "n"(TB));
}
__device__ __forceinline__ void mma_rs(float (&d)[64], const uint32_t* a, uint64_t db, int acc) {
    asm volatile("{\n.reg .pred p;\nsetp.ne.b32 p, %69, 0;\n"
                 "wgmma.mma_async.sync.aligned.m64n128k16.f32.bf16.bf16 " ACC64 ", {%64, %65, %66, %67}, %68, p, 1, 1, 1;\n}"
                 : C64("+f", d) : "r"(a[0]), "r"(a[1]), "r"(a[2]), "r"(a[3]), "l"(db), "r"(acc));
}

__device__ __forceinline__ void stage_tile(const float (&d)[64], float s0, float s1, uint32_t st_addr) {
#pragma unroll
    for (int j = 0; j < 8; j++)
        stsm4((st_addr + (j >> 2) * A_SLOT) ^ ((j & 3) * 32),
              pack_bf16(d[8 * j] * s0, d[8 * j + 1] * s0), pack_bf16(d[8 * j + 2] * s1, d[8 * j + 3] * s1),
              pack_bf16(d[8 * j + 4] * s0, d[8 * j + 5] * s0), pack_bf16(d[8 * j + 6] * s1, d[8 * j + 7] * s1));
}
__device__ __forceinline__ void stage_tile(const float (&d)[64], uint32_t st_addr) {
#pragma unroll
    for (int j = 0; j < 8; j++)
        stsm4((st_addr + (j >> 2) * A_SLOT) ^ ((j & 3) * 32), pack_bf16(d[8 * j], d[8 * j + 1]), pack_bf16(d[8 * j + 2], d[8 * j + 3]),
              pack_bf16(d[8 * j + 4], d[8 * j + 5]), pack_bf16(d[8 * j + 6], d[8 * j + 7]));
}
__device__ __forceinline__ void stage_q(const uint32_t (&p)[32], uint32_t q_addr) {
#pragma unroll
    for (int j = 0; j < 8; j++) stsm4(q_addr + (j >> 2) * A_SLOT + (j & 3) * 256, p[4 * j], p[4 * j + 1], p[4 * j + 2], p[4 * j + 3]);
}
__device__ __forceinline__ void stage_q(const float (&d)[64], uint32_t q_addr) {
#pragma unroll
    for (int j = 0; j < 8; j++)
        stsm4(q_addr + (j >> 2) * A_SLOT + (j & 3) * 256, pack_bf16(d[8 * j], d[8 * j + 1]), pack_bf16(d[8 * j + 2], d[8 * j + 3]),
              pack_bf16(d[8 * j + 4], d[8 * j + 5]), pack_bf16(d[8 * j + 6], d[8 * j + 7]));
}
__device__ __forceinline__ void stash_q(const uint32_t (&p)[32], char* dst) {
#pragma unroll
    for (int j = 0; j < 32; j++) *(uint32_t*)(dst + (j >> 4) * A_SLOT + (j & 1) * 1024 + ((j >> 1) & 7) * 128) = p[j];
}
__device__ __forceinline__ void stash_q(const float (&d)[64], char* dst) {
#pragma unroll
    for (int j = 0; j < 32; j++)
        *(uint32_t*)(dst + (j >> 4) * A_SLOT + (j & 1) * 1024 + ((j >> 1) & 7) * 128) = pack_bf16(d[2 * j], d[2 * j + 1]);
}
__device__ __forceinline__ void write_out(const float (&d)[64], uint32_t st_addr, uint32_t rows, char* out, uint32_t op, int warp, int lane) {
    stage_tile(d, st_addr);
    __syncwarp();
    char* dst = out + ((op_g(op) & 7) * SQ + warp * 16) * (4 * DM) + (op_g(op) >> 3) * (2 * DM) + (op_h(op) & 3) * 512 + (op_takeover(op) ? 0 : 256);
#pragma unroll
    for (int j = 0; j < 8; j++) {
        const int r = (j & 3) * 4 + (lane >> 3);
        uint4 v;
        asm volatile("ld.shared.v4.u32 {%0, %1, %2, %3}, [%4];" : "=r"(v.x), "=r"(v.y), "=r"(v.z), "=r"(v.w)
                     : "r"(rows + (j >> 2) * A_SLOT + r * 128 + (((lane ^ r) & 7) << 4)) : "memory");
        *(uint4*)(dst + r * (4 * DM) + (j >> 2) * 128 + (lane & 7) * 16) = v;
    }
}
__device__ __forceinline__ void publish_tile(uint32_t bar, int lane) {
    asm volatile("fence.proxy.async.shared::cta;" ::: "memory");
    __syncwarp();
    if (lane == 0) mbar_arrive(bar);
}

template <bool INIT>
__device__ __forceinline__ void gemm_step(float (&c)[64], uint64_t a, uint64_t b) {
    if (INIT) mma_ss_init<1>(c, a, b); else mma_ss<1>(c, a, b);
#pragma unroll
    for (int kk = 1; kk < 4; kk++) mma_ss<1>(c, a + DOFF(kk * 32), b + DOFF(kk * 4096));
}

template <bool INIT>
__device__ __forceinline__ void gemm_phase1(float (&c0)[64], uint32_t sb, int wg, int lane, uint32_t& it, int nk) {
    const uint64_t a0 = mk_desc(sb + OFF_A + wg * 8192, 16), b0 = mk_desc(sb + OFF_B, 1024, 2048);
    if (INIT) {
        mbar_wait(sb + BAR_FULL, 0);
        wg_fence();
        gemm_step<true>(c0, a0, b0);
        wg_commit();
        wg_wait<0>();
        if (lane == 0) mbar_arrive(sb + BAR_EMPTY);
        it++;
    }
#pragma unroll 1
    for (int ks = INIT; ks < nk; ks++) {
        const uint32_t s = it & 3;
        mbar_wait(sb + BAR_FULL + s * 8, (it >> 2) & 1);
        wg_fence();
        gemm_step<false>(c0, a0 + s * (A_SLOT >> 4), b0 + s * (B_SLOT >> 4));
        wg_commit();
        wg_wait<0>();
        if (lane == 0) mbar_arrive(sb + BAR_EMPTY + s * 8);
        it++;
    }
    reg_fence(c0);
}

__device__ __forceinline__ void gemm_phase2(float (&c0)[64], float (&c1)[64], const uint32_t (&p)[32], uint32_t sb, int wg, int lane,
                                            uint32_t& it, int nk, uint32_t pend, uint32_t op, uint32_t staged) {
    const uint64_t a0 = mk_desc(sb + OFF_A + wg * 8192, 16), b0 = mk_desc(sb + OFF_B, 1024, 2048);
    char* const stash = (char*)g_o + (threadIdx.x >> 5) * 2048 + lane * 4;
    const uint32_t ph0 = (it >> 2) & 1;
    mbar_wait(sb + BAR_FULL, ph0);
    wg_fence();
    gemm_step<true>(c0, a0, b0);
    wg_commit();
    mbar_wait(sb + BAR_FULL + 8, ph0);
    wg_fence();
    gemm_step<false>(c0, a0 + DOFF(A_SLOT), b0 + DOFF(B_SLOT));
    wg_commit();
    if (pend) {
        stash_q(p, stash + (size_t)pend * 2 * A_SLOT);
        __syncwarp();
        if (lane == 0) mbar_arrive(staged);
    }
    wg_fence();
    gemm_step<true>(c1, a0, b0 + DOFF(16384));
    wg_commit();
    gemm_step<false>(c1, a0 + DOFF(A_SLOT), b0 + DOFF(B_SLOT + 16384));
    wg_commit();
    wg_wait<1>();
    if (lane == 0) mbar_arrive(sb + BAR_EMPTY);
    wg_wait<0>();
    if (lane == 0) mbar_arrive(sb + BAR_EMPTY + 8);
    it += 2;
#pragma unroll 1
    for (int ks = 2; ks < nk - 2; ks++) {
        const uint32_t s = it & 3;
        const uint64_t a = a0 + s * (A_SLOT >> 4), b = b0 + s * (B_SLOT >> 4);
        mbar_wait(sb + BAR_FULL + s * 8, (it >> 2) & 1);
        wg_fence();
#pragma unroll
        for (int kk = 0; kk < 4; kk++) {
            mma_ss<1>(c0, a + DOFF(kk * 32), b + DOFF(kk * 4096));
            mma_ss<1>(c1, a + DOFF(kk * 32), b + DOFF(16384 + kk * 4096));
        }
        wg_commit();
        wg_wait<0>();
        if (lane == 0) mbar_arrive(sb + BAR_EMPTY + s * 8);
        it++;
    }
    const uint32_t ph1 = (it >> 2) & 1, s1 = it & 2;
    const uint64_t a1 = a0 + s1 * (A_SLOT >> 4), b1 = b0 + s1 * (B_SLOT >> 4);
    mbar_wait(sb + BAR_FULL + s1 * 8, ph1);
    wg_fence();
    gemm_step<false>(c0, a1, b1);
    wg_commit();
    mbar_wait(sb + BAR_FULL + s1 * 8 + 8, ph1);
    wg_fence();
    gemm_step<false>(c0, a1 + DOFF(A_SLOT), b1 + DOFF(B_SLOT));
    wg_commit();
    gemm_step<false>(c1, a1, b1 + DOFF(16384));
    gemm_step<false>(c1, a1 + DOFF(A_SLOT), b1 + DOFF(B_SLOT + 16384));
    wg_commit();
    wg_wait<1>();
    reg_fence(c0);
    if (op_type(op) == OP_OT) {
        float4* dst = g_park + op_tile(op) * (12 * 16 * 32) + (threadIdx.x >> 5) * (16 * 32) + lane;
#pragma unroll
        for (int j = 0; j < 16; j++) dst[j * 32] = make_float4(c0[4 * j], c0[4 * j + 1], c0[4 * j + 2], c0[4 * j + 3]);
        __syncwarp();
        if (lane == 0) mbar_arrive(staged);
    } else if (op & Q_STASH) {
        stash_q(c0, stash + (size_t)op_head(op) * 2 * A_SLOT);
    }
    wg_wait<0>();
    reg_fence(c1);
    if (lane == 0) { mbar_arrive(sb + BAR_EMPTY + s1 * 8); mbar_arrive(sb + BAR_EMPTY + s1 * 8 + 8); }
    it += 2;
}

__device__ __forceinline__ void qk_issue(float (&s)[64], uint64_t qa, uint64_t kb) {
    mma_ss_init<0>(s, qa, kb);
#pragma unroll
    for (int kk = 1; kk < 8; kk++)
        mma_ss<0>(s, qa + DOFF((kk >> 2) * A_SLOT + (kk & 3) * 256), kb + DOFF((kk >> 2) * 1024 + (kk & 3) * 32));
}

__device__ __forceinline__ int imax3(float a, float b, float c) {
    return __vimax3_s32(__float_as_int(a), __float_as_int(b), __float_as_int(c));
}

__device__ __forceinline__ void softmax_block(float (&s)[64], uint32_t (&p)[32], float (&o)[64], float& n0, float& n1,
                                              float& l0, float& l1, int never, bool first) {
    constexpr float C = 0.08838834764831845f * 1.4426950408889634f;
    int i0 = imax3(s[0], s[1], s[4]), i1 = imax3(s[2], s[3], s[6]);
    int j0 = imax3(s[5], s[8], s[9]), j1 = imax3(s[7], s[10], s[11]);
#pragma unroll
    for (int j = 3; j < 15; j += 2) {
        i0 = imax3(__int_as_float(i0), s[4 * j], s[4 * j + 1]);
        i1 = imax3(__int_as_float(i1), s[4 * j + 2], s[4 * j + 3]);
        j0 = imax3(__int_as_float(j0), s[4 * j + 4], s[4 * j + 5]);
        j1 = imax3(__int_as_float(j1), s[4 * j + 6], s[4 * j + 7]);
    }
    i0 = imax3(__int_as_float(i0), s[60], s[61]);
    i1 = imax3(__int_as_float(i1), s[62], s[63]);
    i0 = imax3(__int_as_float(i0), __int_as_float(j0), 0.f);
    i1 = imax3(__int_as_float(i1), __int_as_float(j1), 0.f);
    if (__any_sync(0xffffffffu, !(fmaf(__int_as_float(i0), C, n0) <= 8.f && fmaf(__int_as_float(i1), C, n1) <= 8.f))) {
        i0 = max(i0, __shfl_xor_sync(0xffffffffu, i0, 1));
        i1 = max(i1, __shfl_xor_sync(0xffffffffu, i1, 1));
        i0 = max(i0, __shfl_xor_sync(0xffffffffu, i0, 2));
        i1 = max(i1, __shfl_xor_sync(0xffffffffu, i1, 2));
        float x0 = __int_as_float(i0), x1 = __int_as_float(i1);
        if (__any_sync(0xffffffffu, i0 == 0 || i1 == 0)) {
            x0 = x1 = -INFINITY;
#pragma unroll
            for (int j = 0; j < 16; j++) {
                x0 = fmaxf(x0, fmaxf(s[4 * j], s[4 * j + 1]));
                x1 = fmaxf(x1, fmaxf(s[4 * j + 2], s[4 * j + 3]));
            }
            x0 = fmaxf(x0, __shfl_xor_sync(0xffffffffu, x0, 1));
            x1 = fmaxf(x1, __shfl_xor_sync(0xffffffffu, x1, 1));
            x0 = fmaxf(x0, __shfl_xor_sync(0xffffffffu, x0, 2));
            x1 = fmaxf(x1, __shfl_xor_sync(0xffffffffu, x1, 2));
        }
        x0 = fminf(n0, -x0 * C);
        x1 = fminf(n1, -x1 * C);
        if (!first) {
            const float r0 = ex2(x0 - n0), r1 = ex2(x1 - n1);
            l0 *= r0;
            l1 *= r1;
#pragma unroll
            for (int j = 0; j < 32; j++) { o[2 * j] *= (j & 1) ? r1 : r0; o[2 * j + 1] *= (j & 1) ? r1 : r0; }
        }
        n0 = x0;
        n1 = x1;
    }
    float t0 = l0, t1 = l1, u0 = 0.f, u1 = 0.f;
    constexpr int LAG = 2;
#pragma unroll
    for (int c = -1; c < 32 + LAG; c++) {
        if (c >= 0 && c < 32) { s[2 * c] = ex2(s[2 * c]); s[2 * c + 1] = ex2(s[2 * c + 1]); }
        if (c + 1 < 32) {
            const int j = c + 1;
            s[2 * j] = fmaf(s[2 * j], C, (j & 1) ? n1 : n0);
            s[2 * j + 1] = fmaf(s[2 * j + 1], C, (j & 1) ? n1 : n0);
        }
        if (c >= LAG) {
            const int j = c - LAG;
            if (j & 1) { t1 += s[2 * j]; if (j == 1) u1 = s[3]; else u1 += s[2 * j + 1]; }
            else { t0 += s[2 * j]; if (j == 0) u0 = s[1]; else u0 += s[2 * j + 1]; }
            p[j] = pack_bf16(s[2 * j], s[2 * j + 1]);
        }
        if (c >= 0 && c < 31) {
#pragma unroll
            for (int i = 0; i < 64; i++) if (i >= 2 * (c - LAG + 1)) asm volatile("" : "+f"(s[i]));
#pragma unroll
            for (int i = 0; i < 32; i++) if (i < c - LAG + 1) asm volatile("" : "+r"(p[i]));
            asm volatile("" : "+f"(t0), "+f"(t1), "+f"(u0), "+f"(u1));
            SCHED_FENCE(never);
        }
    }
    l0 = t0 + u0;
    l1 = t1 + u1;
}

__device__ __forceinline__ void attn_epilogue(float (&o)[64], float l0, float l1, uint32_t st_addr) {
    l0 += __shfl_xor_sync(0xffffffffu, l0, 1);
    l1 += __shfl_xor_sync(0xffffffffu, l1, 1);
    l0 += __shfl_xor_sync(0xffffffffu, l0, 2);
    l1 += __shfl_xor_sync(0xffffffffu, l1, 2);
    stage_tile(o, __fdividef(1.f, l0), __fdividef(1.f, l1), st_addr);
}

__global__ void __launch_bounds__(NTHREADS, 1) mha2_kernel(const __grid_constant__ Params prm) {
    extern __shared__ __align__(1024) char smem_raw[];
    const uint32_t sb = smem_u32(smem_raw);
    const int tid = threadIdx.x, lane = tid & 31;
    const int warp = __shfl_sync(0xffffffffu, tid >> 5, 0);
    const int cta = blockIdx.x;
    const uint16_t* ops = prm.ops[cta];

    if (warp == 12 && elect_one()) {
        for (int i = 0; i < 4; i++) mbar_init(sb + BAR_FULL + 8 * i, 1);
        asm volatile("fence.mbarrier_init.release.cluster;" ::: "memory");
        const uint32_t op = ops[0], br = op_g(op) >> 3;
        const bool two = op & Q_TWO;
#pragma unroll 1
        for (int s = 0; s < 4; s++) {
            mbar_expect_tx(sb + BAR_FULL + s * 8, two ? A_SLOT + B_SLOT : A_SLOT + B_SLOT / 2);
            tma_2d(sb + OFF_A + s * A_SLOT, &prm.x[br], s * 64, (op_g(op) & 7) * SQ, sb + BAR_FULL + s * 8);
            tma_w(sb + OFF_B + s * B_SLOT, &prm.wq[br], s * 64, op_h(op) * 2, sb + BAR_FULL + s * 8);
            if (two) tma_w(sb + OFF_B + s * B_SLOT + 16384, &prm.wq[br], s * 64, op_h(op) * 2 + 2, sb + BAR_FULL + s * 8);
        }
        asm volatile("prefetch.tensormap [%0];" ::"l"(&prm.k[br]) : "memory");
        asm volatile("prefetch.tensormap [%0];" ::"l"(&prm.v[br]) : "memory");
    }
    if (tid == 0) {
        for (int i = 0; i < 4; i++) mbar_init(sb + BAR_EMPTY + 8 * i, 12);
        for (int i = 0; i < 2; i++) mbar_init(sb + BAR_QFREE + 8 * i, 3);
        for (int i = 0; i < 3; i++) {
            mbar_init(sb + BAR_STAGED + 8 * i, 4);
            mbar_init(sb + BAR_QREADY + 8 * i, 1);
        }
        asm volatile("fence.mbarrier_init.release.cluster;" ::: "memory");
    }
    __syncthreads();

    if (warp >= 12) {
        asm volatile("setmaxnreg.dec.sync.aligned.u32 32;");
        const unsigned epoch0 = g_epoch[cta];
        if (warp == 12) {
            uint32_t it = 4;
            bool after_att = false;
#pragma unroll 1
            for (int i = 0;; i++) {
                const uint32_t op = __shfl_sync(0xffffffffu, (uint32_t)ops[i], 0);
                const uint32_t ty = op_type(op), g = op_g(op), h = op_h(op), br = g >> 3;
                if (ty == OP_END) break;
                if (ty == OP_AT) {
                    const int row0 = ((g & 7) * NH + h) * SK;
#pragma unroll 1
                    for (int t = 0; t < 16; t++, it++) {
                        const uint32_t s = it & 3;
                        mbar_wait_sleep(sb + BAR_EMPTY + s * 8, ((it >> 2) & 1) ^ 1);
                        if (it == 16 && h < 4) {
                            const uint32_t c0 = clock();
                            while ((uint32_t)clock() - c0 < h * STAG) __nanosleep(50);
                        }
                        if (elect_one()) {
                            mbar_expect_tx(sb + BAR_FULL + s * 8, B_SLOT);
                            tma_4d_stream(sb + OFF_B + s * B_SLOT, (t & 1) ? &prm.v[br] : &prm.k[br], (row0 + (t >> 1) * 128) / 8,
                                          sb + BAR_FULL + s * 8);
                        }
                    }
                    after_att = true;
                } else if (ty == OP_Q) {
                    const bool two = op & Q_TWO;
#pragma unroll 1
                    for (int ks = it & 15; ks < 16; ks++, it++) {
                        const uint32_t s = it & 3;
                        if (after_att && (ks == 0 || ks == 2)) mbar_wait_sleep(sb + BAR_QFREE + ks * 4, 0);
                        mbar_wait_sleep(sb + BAR_EMPTY + s * 8, ((it >> 2) & 1) ^ 1);
                        if (elect_one()) {
                            mbar_expect_tx(sb + BAR_FULL + s * 8, two ? A_SLOT + B_SLOT : A_SLOT + B_SLOT / 2);
                            tma_2d(sb + OFF_A + s * A_SLOT, &prm.x[br], ks * 64, (g & 7) * SQ, sb + BAR_FULL + s * 8);
                            tma_w(sb + OFF_B + s * B_SLOT, &prm.wq[br], ks * 64, h * 2, sb + BAR_FULL + s * 8);
                            if (two) tma_w(sb + OFF_B + s * B_SLOT + 16384, &prm.wq[br], ks * 64, h * 2 + 2, sb + BAR_FULL + s * 8);
                        }
                    }
                    after_att = false;
                } else {
                    unsigned epoch3;
                    asm volatile("mad.lo.u32 %0, %1, 3, 3;" : "=r"(epoch3) : "r"(epoch0));
                    const char* osrc = (const char*)g_o + (size_t)g * NH * 2 * A_SLOT;
                    const int k1 = op_k1(op), k0 = op_takeover(op) ? k1 : 0, col = (h & 3) * 4;
                    const bool own = k0 >= 48;
                    const uint32_t hown = 28 + (h & 3);
                    uint32_t ready = 0;
#pragma unroll 1
                    for (int ks = k0; ks < 64; ks++, it++) {
                        const uint32_t s = it & 3;
                        const bool have_a = own && ks < k0 + 2;
                        uint32_t hk = ks >> 1;
                        if (own && hk <= hown) hk = have_a ? hown : hk - 1;
                        const int kk = hk * 2 + (ks & 1);
                        if (k0 && ks == 60) flag_wait(g_pflag + op_tile(op), epoch3);
                        mbar_wait_sleep(sb + BAR_EMPTY + s * 8, ((it >> 2) & 1) ^ 1);
                        if (elect_one()) {
                            mbar_expect_tx(sb + BAR_FULL + s * 8, (have_a ? 0 : A_SLOT) + (ks < k1 ? B_SLOT : B_SLOT / 2));
                            tma_w(sb + OFF_B + s * B_SLOT, &prm.wo[br], kk * 64, (ks < k1 || k0) ? col : col + 2, sb + BAR_FULL + s * 8);
                            if (ks < k1) tma_w(sb + OFF_B + s * B_SLOT + 16384, &prm.wo[br], kk * 64, col + 2, sb + BAR_FULL + s * 8);
                            if (ks >= 40 && ks < 56 && !k0) tma_prefetch_w(&prm.wo[br], (36 + (ks >> 1)) * 64, col + (ks & 1) * 2);
                        }
                        if (have_a) continue;
                        if (!((ready >> hk) & 1)) {
                            ready = flag_wait_any(g_flag + g * NH + lane, epoch3, 1u << hk);
                            __syncwarp();
                            asm volatile("fence.proxy.async.global;" ::: "memory");
                        }
                        if (after_att && ks == k0 + (own ? 4 : 0)) mbar_wait_sleep(sb + BAR_QFREE, 0);
                        if (after_att && ks == k0 + 2) mbar_wait_sleep(sb + BAR_QFREE + 8, 0);
                        if (elect_one()) bulk_load(sb + OFF_A + s * A_SLOT, osrc + (size_t)kk * A_SLOT, A_SLOT, sb + BAR_FULL + s * 8);
                    }
                }
            }
        } else {
            const int w = warp - 13;
            const unsigned epoch = epoch0 + 1;
#pragma unroll 1
            for (int i = 0;; i++) {
                const uint32_t op = __shfl_sync(0xffffffffu, (uint32_t)ops[i], 0);
                const uint32_t ty = op_type(op);
                if (ty == OP_END || (ty == OP_OT && op_takeover(op))) break;
                const uint32_t n1 = __shfl_sync(0xffffffffu, (uint32_t)ops[i + 1], 0);
                const bool more = op_type(n1) == OP_AT && !(n1 & AT_LAST);
                mbar_wait_sleep(sb + BAR_STAGED + w * 8, i & 1);
                if (lane == 0) {
                    if (ty == OP_Q) {
                        if (op & Q_STASH) {
                            __threadfence();
                            asm volatile("st.relaxed.gpu.global.u32 [%0], %1;" ::"l"(g_qflag + op_head(op) * 4 + w), "r"(epoch) : "memory");
                            if (op & Q_STASH1) asm volatile("st.relaxed.gpu.global.u32 [%0], %1;" ::"l"(g_qflag + op_head(op) * 4 + 4 + w), "r"(epoch) : "memory");
                            else mbar_arrive(sb + BAR_QFREE);
                        }
                    } else if (ty == OP_AT) {
                        char* dst = (char*)g_o + (size_t)op_head(op) * 2 * A_SLOT + w * 8192;
                        const uint32_t src = sb + OFF_A + ((op & AT_BUF1) ? 2 * A_SLOT : 0) + w * 8192;
                        bulk_store_stream(dst, src, 8192);
                        bulk_store_stream(dst + A_SLOT, src + A_SLOT, 8192);
                        asm volatile("cp.async.bulk.commit_group;" ::: "memory");
                        asm volatile("cp.async.bulk.wait_group 0;" ::: "memory");
                        if (!more) mbar_arrive(sb + BAR_QFREE + ((op & AT_BUF1) ? 8 : 0));
                        asm volatile("red.release.gpu.global.add.u32 [%0], 1;" ::"l"(g_flag + op_head(op)) : "memory");
                    } else {
                        asm volatile("red.release.gpu.global.add.u32 [%0], 1;" ::"l"(g_pflag + op_tile(op)) : "memory");
                    }
                }
                __syncwarp();
                if (!more) continue;
                const uint32_t n2 = __shfl_sync(0xffffffffu, (uint32_t)ops[i + 2], 0);
                if (!(n2 & AT_STASH)) continue;
                if (lane == 0) {
                    flag_wait(g_qflag + op_head(n2) * 4 + w, epoch);
                    asm volatile("fence.proxy.async.global;" ::: "memory");
                    const uint32_t buf = sb + OFF_A + ((n2 & AT_BUF1) ? 2 * A_SLOT : 0) + w * 8192;
                    const char* src = (const char*)g_o + (size_t)op_head(n2) * 2 * A_SLOT + w * 8192;
                    mbar_expect_tx(sb + BAR_QREADY + w * 8, 16384);
                    bulk_load_stream(buf, src, 8192, sb + BAR_QREADY + w * 8);
                    bulk_load_stream(buf + A_SLOT, src + A_SLOT, 8192, sb + BAR_QREADY + w * 8);
                }
                __syncwarp();
            }
        }
        asm volatile("bar.sync 4, 128;" ::: "memory");
        if (tid == 384) g_epoch[cta] = epoch0 + 1;

    } else {
        asm volatile("setmaxnreg.inc.sync.aligned.u32 160;");
        const int wg = warp >> 2;
        const int my_bar = 1 + wg, next_bar = wg == 2 ? 1 : 2 + wg;
        const uint32_t qa0 = sb + OFF_A + wg * 8192;
        const uint32_t st_addr = qa0 + ((warp & 3) * 16 + (lane & 15)) * 128 + (((lane >> 4) ^ (lane & 7)) << 4);
#define Q_ADDR (sb + OFF_A + warp * 2048 + ((lane >> 3) & 1) * 1024 + (lane >> 4) * 128 + (lane & 7) * 16)
        const uint32_t staged = sb + BAR_STAGED + wg * 8;
        const uint64_t qd0 = mk_desc(qa0, 128) & ~(3ull << 62);
        const uint64_t kd0 = mk_desc(sb + OFF_B, 16, 2048), vd0 = mk_desc(sb + OFF_B, 1024, 2048);
        float o[64], s[64];
        uint32_t p[32];
        uint32_t it = 0, pend = 0;
        int i = 0;
#pragma unroll
        for (int j = 0; j < 32; j++) p[j] = 0;
#pragma unroll 1
        for (;;) {
            const uint32_t op = __shfl_sync(0xffffffffu, (uint32_t)ops[i], 0);
            if (op_type(op) == OP_END) break;
            if (op_type(op) != OP_AT) {
                if (op_type(op) == OP_Q && !(op & Q_TWO)) {
                    gemm_phase1<true>(o, sb, wg, lane, it, 16);
                    stage_q(o, Q_ADDR);
                    publish_tile(staged, lane);
                } else if (op_type(op) == OP_OT && op_takeover(op)) {
#pragma unroll
                    for (int j = 0; j < 64; j++) s[j] = 0.f;
                    reg_fence(s);
                    asm volatile("bar.sync %0, 128;" ::"r"(5 + wg) : "memory");
                    gemm_phase1<false>(s, sb, wg, lane, it, 60 - op_k1(op));
                    const float4* src = g_park + op_tile(op) * (12 * 16 * 32) + (tid >> 5) * (16 * 32) + lane;
                    const uint64_t a0 = mk_desc(qa0, 16), b0 = mk_desc(sb + OFF_B, 1024, 2048);
#pragma unroll
                    for (int ks = 0; ks < 4; ks++) {
                        const uint32_t sl = it & 3;
                        mbar_wait(sb + BAR_FULL + sl * 8, (it >> 2) & 1);
                        wg_fence();
                        gemm_step<false>(s, a0 + sl * (A_SLOT >> 4), b0 + sl * (B_SLOT >> 4));
                        wg_commit();
                        it++;
#pragma unroll
                        for (int j = 4 * ks; j < 4 * ks + 4; j++) {
                            const float4 v = __ldcg(src + j * 32);
                            o[4 * j] = v.x; o[4 * j + 1] = v.y; o[4 * j + 2] = v.z; o[4 * j + 3] = v.w;
                        }
                    }
                    wg_wait<0>();
                    reg_fence(s);
#pragma unroll
                    for (int j = 0; j < 64; j++) s[j] += o[j];
                    write_out(s, st_addr, sb + OFF_A + warp * 2048, prm.out, op, warp, lane);
                    break;
                } else {
                    gemm_phase2(o, s, p, sb, wg, lane, it, op_type(op) == OP_Q ? 16 : op_k1(op), pend, op, staged);
                    if (op_type(op) == OP_OT) {
                        gemm_phase1<false>(s, sb, wg, lane, it, 64 - op_k1(op));
                        write_out(s, st_addr, sb + OFF_A + warp * 2048, prm.out, op, warp, lane);
                        break;
                    }
#pragma unroll
                    for (int j = 0; j < 32; j++) p[j] = pack_bf16(s[2 * j], s[2 * j + 1]);
                    pend = 0;
                    if (op & Q_STASH1) {
                        pend = op_head(op) + 1;
                    } else {
                        if (!(op & Q_STASH)) stage_q(o, Q_ADDR);
                        stage_q(p, Q_ADDR + 2 * A_SLOT);
                        publish_tile(staged, lane);
                    }
                }
                i++;
                continue;
            }
            float n0 = INFINITY, n1 = INFINITY, l0 = 0.f, l1 = 0.f;
            int t = (op & AT_BUF1) ? 8 : 0, tend = (t + 8) | ((ops[i + 1] & AT_STASH) ? 8 << 8 : 16 << 8);
            while (!(ops[i++] & AT_LAST)) tend += 8;
            tend = __shfl_sync(0xffffffffu, tend, 0);
            if (wg == 2) bar_arrive(1);
            mbar_wait(sb + BAR_FULL, (it >> 2) & 1);
            bar_sync(my_bar);
            wg_fence();
            qk_issue(s, qd0 + t * (2 * A_SLOT / 128), kd0);
            wg_commit();
            bar_arrive(next_bar);
            wg_wait<0>();
            reg_fence(s);
            if (lane == 0) mbar_arrive(sb + BAR_EMPTY);
            it++;
            softmax_block(s, p, o, n0, n1, l0, l1, prm.never, true);
#pragma unroll 1
            for (t++; t != (tend & 255); t++) {
                const bool flip = (t & 7) == 0;
                if (flip && t >= (tend >> 8)) mbar_wait(sb + BAR_QREADY + wg * 8, ((t - (tend >> 8)) >> 3) & 1);
                const uint32_t sv = it & 3, sk = (it + 1) & 3;
                const uint64_t vb = vd0 + sv * (B_SLOT >> 4), kb = kd0 + sk * (B_SLOT >> 4), qd = qd0 + (t & 8) * (2 * A_SLOT / 128);
                mbar_wait(sb + BAR_FULL + sv * 8, (it >> 2) & 1);
                bar_sync(my_bar);
                wg_fence();
                mma_rs(o, p, vb, (t & 7) != 1);
#pragma unroll
                for (int kk = 1; kk < 7; kk++) mma_rs(o, p + 4 * kk, vb + DOFF(kk * 4096), 1);
                wg_commit();
                mma_rs(o, p + 28, vb + DOFF(7 * 4096), 1);
                wg_commit();
                mbar_wait(sb + BAR_FULL + sk * 8, ((it + 1) >> 2) & 1);
                wg_wait<1>();
                wg_fence();
                qk_issue(s, qd, kb);
                wg_commit();
                bar_arrive(next_bar);
                wg_wait<1>();
                reg_fence(o);
                if (lane == 0) mbar_arrive(sb + BAR_EMPTY + sv * 8);
                if (flip) {
                    attn_epilogue(o, l0, l1, st_addr + (~t & 8) * (2 * A_SLOT / 8));
                    publish_tile(staged, lane);
                    n0 = n1 = INFINITY;
                    l0 = l1 = 0.f;
                }
                wg_wait<0>();
                reg_fence(s);
                if (lane == 0) mbar_arrive(sb + BAR_EMPTY + sk * 8);
                it += 2;
                softmax_block(s, p, o, n0, n1, l0, l1, prm.never, flip);
            }
            {
                const uint64_t vb = vd0 + DOFF(3 * B_SLOT);
                mbar_wait(sb + BAR_FULL + 3 * 8, (it >> 2) & 1);
                bar_sync(my_bar);
                wg_fence();
#pragma unroll
                for (int kk = 0; kk < 8; kk++) mma_rs(o, p + 4 * kk, vb + DOFF(kk * 4096), 1);
                wg_commit();
                if (wg != 2) bar_arrive(next_bar);
                wg_wait<0>();
                reg_fence(o);
                if (lane == 0) mbar_arrive(sb + BAR_EMPTY + 3 * 8);
                it++;
                attn_epilogue(o, l0, l1, st_addr + (~t & 8) * (2 * A_SLOT / 8));
                publish_tile(staged, lane);
            }
        }
    }
}

void build_schedule(uint16_t (*ops)[MAXOPS]) {
    for (int c = 0; c < NCTA; c++) for (int j = 0; j < MAXOPS; j++) ops[c][j] = OP_END;
    auto mk = [](uint32_t ty, int g, int h, uint32_t fl) { return (uint16_t)(ty | (g << 2) | (h << 6) | fl); };
    auto ncta = [](int g, int j) { return g * 8 + (j & 1) + (j >> 1) * 4; };
    auto mcta = [](int g, int j) { return g * 8 + 2 + (j & 1) + (j >> 1) * 4; };
    static const char* const plan[4][4] = {{"paas", "ssss", "ssss", "sssx"}, {"mass", "ssma", "ssss", "ssss"},
                                           {"mass", "ssma", "ssss", "ssss"}, {"spaa", "sssss", "paas", "ssss"}};
    for (int g = 0; g < 16; g++) {
        const int q = g & 3;
        uint16_t* oe = ops[128 + (g >> 2)];
        int st[28], ns = 0, h = 4;
        for (int sl = 0; sl < 5; sl++) {
            for (int j = 0; j < 4; j++) {
                uint16_t* o = ops[mcta(g, j)];
                const char c = plan[q][j][sl];
                if (c == 's') { o[sl] = mk(OP_Q, g, h, Q_TWO | Q_STASH | Q_STASH1); st[ns++] = h; st[ns++] = h + 1; }
                if (c == 'm') { o[sl] = mk(OP_Q, g, h, Q_TWO | Q_STASH); o[sl + 1] = mk(OP_AT, g, h + 1, AT_BUF1 | AT_LAST); st[ns++] = h; }
                if (c == 'p') { o[sl] = mk(OP_Q, g, h, Q_TWO); o[sl + 1] = mk(OP_AT, g, h, 0); o[sl + 2] = mk(OP_AT, g, h + 1, AT_BUF1 | AT_LAST); }
                if (c == 'x') o[sl] = mk(OP_Q, g + 3, 28, Q_TWO | Q_STASH | Q_STASH1);
                if (c == 's' || c == 'm' || c == 'p') h += 2;
                if (q == 3 && h == 28) { st[ns++] = h; st[ns++] = h + 1; h += 2; }
            }
            if (q == 0 && sl == 0) {
                oe[0] = mk(OP_Q, g, h, Q_TWO);
                oe[1] = mk(OP_AT, g, h, 0);
                oe[2] = mk(OP_AT, g, h + 1, AT_BUF1);
                h += 2;
            }
        }
        const int pos0 = q == 1 ? 2 : q == 2 ? 4 : 0, pos1 = q == 1 ? 3 : q == 2 ? 6 : 0;
        int k = 0;
        for (int w = 0; w < 7; w++) {
            if (w && pos0 == w) oe[2 * q + 1] = mk(OP_AT, g, st[k++], AT_STASH);
            if (w && pos1 == w) oe[2 * q + 2] = mk(OP_AT, g, st[k++], AT_STASH | AT_BUF1 | (q == 2 ? AT_LAST : 0));
            for (int j = 0; j < 4; j++) {
                uint16_t* o = ops[ncta(g, j)];
                if (w == 0) { o[0] = mk(OP_Q, g, j, 0); o[1] = mk(OP_AT, g, j, 0); }
                else o[w + 1] = mk(OP_AT, g, st[k++], AT_STASH | ((w & 1) ? AT_BUF1 : 0) | (w == 6 ? AT_LAST : 0));
            }
        }
        for (int j = 0; j < 4; j++) {
            if (plan[q][j][4]) {
                ops[mcta(g, j)][5] = mk(OP_OT, g, j, (K1E / 2) << 11);
                oe[7] = mk(OP_OT, g, 4 | j, (K1E / 2) << 11);
            } else {
                ops[mcta(g, j)][4] = mk(OP_OT, g, j, (K1N / 2) << 11);
                ops[ncta(g, j)][8] = mk(OP_OT, g, 4 | j, (K1N / 2) << 11);
            }
        }
    }
}

typedef CUresult (*EncodeFn)(CUtensorMap*, CUtensorMapDataType, cuuint32_t, void*, const cuuint64_t*, const cuuint64_t*,
                             const cuuint32_t*, const cuuint32_t*, CUtensorMapInterleave, CUtensorMapSwizzle,
                             CUtensorMapL2promotion, CUtensorMapFloatOOBfill);

void encode(EncodeFn fn, CUtensorMap* m, void* ptr, int rank, const cuuint64_t* dims, const cuuint64_t* strides, const cuuint32_t* box) {
    const cuuint32_t es[4] = {1, 1, 1, 1};
    fn(m, CU_TENSOR_MAP_DATA_TYPE_BFLOAT16, rank, ptr, dims, strides, box, es, CU_TENSOR_MAP_INTERLEAVE_NONE,
       CU_TENSOR_MAP_SWIZZLE_128B, CU_TENSOR_MAP_L2_PROMOTION_NONE, CU_TENSOR_MAP_FLOAT_OOB_FILL_NONE);
}

}

extern "C" void kernel_launch(void* const* d_in, const int* in_sizes, int n_in, void* d_out, int out_size) {
    static EncodeFn fn = nullptr;
    if (!fn) {
        cudaDriverEntryPointQueryResult qr;
        void* p = nullptr;
        cudaGetDriverEntryPoint("cuTensorMapEncodeTiled", &p, cudaEnableDefault, &qr);
        fn = (EncodeFn)p;
        cudaFuncSetAttribute(mha2_kernel, cudaFuncAttributeMaxDynamicSharedMemorySize, SMEM_BYTES);
    }
    Params prm;
    for (int br = 0; br < 2; br++) {
        void* x = d_in[5 * br + 0];
        void* k = d_in[5 * br + 1];
        void* v = d_in[5 * br + 2];
        void* wq = d_in[5 * br + 3];
        void* wo = d_in[5 * br + 4];
        {
            cuuint64_t dims[2] = {DM, NB * SQ}, st[1] = {DM * 2};
            cuuint32_t box[2] = {64, SQ};
            encode(fn, &prm.x[br], x, 2, dims, st, box);
        }
        {
            cuuint64_t dims[4] = {64, 8, NH * DH / 64, DM / 8}, st[3] = {NH * DH * 2, 128, 8 * NH * DH * 2};
            cuuint32_t box[4] = {64, 8, 2, 8};
            encode(fn, &prm.wq[br], wq, 4, dims, st, box);
        }
        {
            cuuint64_t dims[4] = {64, 8, 2, (cuuint64_t)NB * NH * SK / 8}, st[3] = {DH * 2, 128, 8 * DH * 2};
            cuuint32_t box[4] = {64, 8, 2, 16};
            encode(fn, &prm.k[br], k, 4, dims, st, box);
            encode(fn, &prm.v[br], v, 4, dims, st, box);
        }
        {
            cuuint64_t dims[4] = {64, 8, DM / 64, NH * DH / 8}, st[3] = {DM * 2, 128, 8 * DM * 2};
            cuuint32_t box[4] = {64, 8, 2, 8};
            encode(fn, &prm.wo[br], wo, 4, dims, st, box);
        }
    }
    prm.never = 0;
    prm.out = (char*)d_out;
    build_schedule(prm.ops);
    mha2_kernel<<<NCTA, NTHREADS, SMEM_BYTES>>>(prm);
}
```

```cpp
#include <cuda_runtime.h>
#include <cuda_bf16.h>
#include <cuda.h>
#include <stdint.h>

namespace {

constexpr int NB = 8, SQ = 192, DM = 1024, NH = 32, SK = 1024, DH = 128;
constexpr int NCTA = 132;
constexpr int MAXOPS = 10;
constexpr int NTHREADS = 512;
constexpr int K1N = 56;
constexpr int K1E = 34;
constexpr uint32_t STAG = 800;

constexpr uint32_t A_SLOT = 24576;
constexpr uint32_t B_SLOT = 32768;
constexpr uint32_t OFF_A = 0;
constexpr uint32_t OFF_B = 4 * A_SLOT;
constexpr uint32_t OFF_BAR = OFF_B + 4 * B_SLOT;
constexpr uint32_t BAR_FULL = OFF_BAR;
constexpr uint32_t BAR_EMPTY = OFF_BAR + 32;
constexpr uint32_t BAR_QFREE = OFF_BAR + 64;
constexpr uint32_t BAR_STAGED = OFF_BAR + 80;
constexpr uint32_t BAR_QREADY = OFF_BAR + 104;
constexpr uint32_t OFF_OPS = OFF_BAR + 128;
constexpr uint32_t SMEM_BYTES = OFF_BAR + 160;

struct Params {
    CUtensorMap x[2], wq[2], k[2], v[2], wo[2];
    char* out;
    int never;
    uint16_t ops[NCTA][MAXOPS];
};

enum : uint32_t { OP_END = 0, OP_Q = 1, OP_AT = 2, OP_OT = 3 };
enum : uint32_t { Q_TWO = 1u << 11, Q_STASH = 1u << 12, Q_STASH1 = 1u << 13,
                  AT_STASH = 1u << 11, AT_BUF1 = 1u << 12, AT_LAST = 1u << 13 };
__host__ __device__ constexpr uint32_t op_type(uint32_t op) { return op & 3; }
__host__ __device__ constexpr uint32_t op_g(uint32_t op) { return (op >> 2) & 15; }
__host__ __device__ constexpr uint32_t op_h(uint32_t op) { return (op >> 6) & 31; }
__host__ __device__ constexpr uint32_t op_head(uint32_t op) { return op_g(op) * NH + op_h(op); }
__host__ __device__ constexpr uint32_t op_k1(uint32_t op) { return (op >> 11) * 2; }
__host__ __device__ constexpr bool op_takeover(uint32_t op) { return (op >> 8) & 1; }
__host__ __device__ constexpr uint32_t op_tile(uint32_t op) { return op_g(op) * 4 + ((op >> 6) & 3); }

__device__ __align__(1024) uint4 g_o[2 * NB * NH * 2 * (A_SLOT / 16)];
__device__ __align__(1024) float4 g_park[64 * 12 * 16 * 32];
__device__ unsigned g_flag[2 * NB * NH];
__device__ unsigned g_qflag[2 * NB * NH * 4];
__device__ unsigned g_pflag[64];
__device__ unsigned g_epoch[NCTA];

__device__ __forceinline__ uint32_t smem_u32(const void* p) { return (uint32_t)__cvta_generic_to_shared(p); }
__device__ __forceinline__ void mbar_init(uint32_t bar, uint32_t cnt) {
    asm volatile("mbarrier.init.shared::cta.b64 [%0], %1;" ::"r"(bar), "r"(cnt) : "memory");
}
__device__ __forceinline__ void mbar_expect_tx(uint32_t bar, uint32_t bytes) {
    asm volatile("mbarrier.arrive.expect_tx.shared::cta.b64 _, [%0], %1;" ::"r"(bar), "r"(bytes) : "memory");
}
__device__ __forceinline__ void mbar_arrive(uint32_t bar) {
    asm volatile("mbarrier.arrive.shared::cta.b64 _, [%0];" ::"r"(bar) : "memory");
}
__device__ __forceinline__ void mbar_wait(uint32_t bar, uint32_t parity) {
    asm volatile(
        "{\n.reg .pred p;\n.reg .u32 n;\nmov.u32 n, 0;\n"
        "LAB_WAIT:\n"
        "mbarrier.try_wait.parity.shared::cta.b64 p, [%0], %1;\n"
        "@p bra LAB_DONE;\n"
        "add.u32 n, n, 1;\nsetp.lt.u32 p, n, 0x2000000;\n@p bra LAB_WAIT;\ntrap;\n"
        "LAB_DONE:\n}" ::"r"(bar), "r"(parity) : "memory");
}
__device__ __forceinline__ void mbar_wait_sleep(uint32_t bar, uint32_t parity) {
    asm volatile(
        "{\n.reg .pred p;\n.reg .u32 n;\nmov.u32 n, 0;\n"
        "LAB_WAIT:\n"
        "mbarrier.try_wait.parity.shared::cta.b64 p, [%0], %1, 20000;\n"
        "@p bra LAB_DONE;\n"
        "add.u32 n, n, 1;\nsetp.lt.u32 p, n, 0x20000;\n@p bra LAB_WAIT;\ntrap;\n"
        "LAB_DONE:\n}" ::"r"(bar), "r"(parity) : "memory");
}
__device__ __forceinline__ void flag_wait(const unsigned* p, unsigned target) {
    asm volatile(
        "{\n.reg .pred p;\n.reg .u32 n, v;\n.reg .s32 d;\nmov.u32 n, 0;\n"
        "LAB_WAIT:\n"
        "ld.acquire.gpu.global.u32 v, [%0];\n"
        "sub.s32 d, v, %1;\nsetp.ge.s32 p, d, 0;\n"
        "@p bra LAB_DONE;\n"
        "nanosleep.u32 64;\n"
        "add.u32 n, n, 1;\nsetp.lt.u32 p, n, 0x400000;\n@p bra LAB_WAIT;\ntrap;\n"
        "LAB_DONE:\n}" ::"l"(p), "r"(target) : "memory");
}
__device__ __forceinline__ uint32_t flag_wait_any(const unsigned* p, unsigned target, uint32_t mask) {
    uint32_t r;
    asm volatile(
        "{\n.reg .pred p;\n.reg .u32 n, v;\n.reg .s32 d;\nmov.u32 n, 0;\n"
        "LAB_WAIT:\n"
        "ld.acquire.gpu.global.u32 v, [%1];\n"
        "sub.s32 d, v, %2;\nsetp.ge.s32 p, d, 0;\n"
        "vote.sync.ballot.b32 %0, p, 0xffffffff;\n"
        "and.b32 v, %0, %3;\nsetp.ne.u32 p, v, 0;\n"
        "@p bra LAB_DONE;\n"
        "nanosleep.u32 32;\n"
        "add.u32 n, n, 1;\nsetp.lt.u32 p, n, 0x400000;\n@p bra LAB_WAIT;\ntrap;\n"
        "LAB_DONE:\n}" : "=&r"(r) : "l"(p), "r"(target), "r"(mask) : "memory");
    return r;
}
__device__ __forceinline__ uint64_t policy_evict_first() {
    uint64_t r;
    asm("createpolicy.fractional.L2::evict_first.b64 %0, 1.0;" : "=l"(r));
    return r;
}
__device__ __forceinline__ void tma_2d(uint32_t dst, const CUtensorMap* m, int c0, int c1, uint32_t bar) {
    asm volatile("cp.async.bulk.tensor.2d.shared::cluster.global.mbarrier::complete_tx::bytes [%0], [%1, {%3, %4}], [%2];"
                 ::"r"(dst), "l"(m), "r"(bar), "r"(c0), "r"(c1) : "memory");
}
__device__ __forceinline__ void tma_w(uint32_t dst, const CUtensorMap* m, int k, int c, uint32_t bar) {
    asm volatile("cp.async.bulk.tensor.4d.shared::cluster.global.mbarrier::complete_tx::bytes [%0], [%1, {0, 0, %3, %4}], [%2];"
                 ::"r"(dst), "l"(m), "r"(bar), "r"(c), "r"(k >> 3) : "memory");
}
__device__ __forceinline__ void tma_4d_stream(uint32_t dst, const CUtensorMap* m, int c3, uint32_t bar) {
    asm volatile("cp.async.bulk.tensor.4d.shared::cluster.global.mbarrier::complete_tx::bytes.L2::cache_hint [%0], [%1, {0, 0, 0, %3}], [%2], %4;"
                 ::"r"(dst), "l"(m), "r"(bar), "r"(c3), "l"(policy_evict_first()) : "memory");
}
__device__ __forceinline__ void tma_prefetch_w(const CUtensorMap* m, int k, int c) {
    asm volatile("cp.async.bulk.prefetch.tensor.4d.L2.global [%0, {0, 0, %1, %2}];" ::"l"(m), "r"(c), "r"(k >> 3) : "memory");
}
__device__ __forceinline__ void bulk_load(uint32_t dst, const void* src, uint32_t bytes, uint32_t bar) {
    asm volatile("cp.async.bulk.shared::cluster.global.mbarrier::complete_tx::bytes [%0], [%1], %2, [%3];"
                 ::"r"(dst), "l"(src), "r"(bytes), "r"(bar) : "memory");
}
__device__ __forceinline__ void bulk_load_stream(uint32_t dst, const void* src, uint32_t bytes, uint32_t bar) {
    asm volatile("cp.async.bulk.shared::cluster.global.mbarrier::complete_tx::bytes.L2::cache_hint [%0], [%1], %2, [%3], %4;"
                 ::"r"(dst), "l"(src), "r"(bytes), "r"(bar), "l"(policy_evict_first()) : "memory");
}
__device__ __forceinline__ void bulk_store_stream(void* dst, uint32_t src, uint32_t bytes) {
    asm volatile("cp.async.bulk.global.shared::cta.bulk_group.L2::cache_hint [%0], [%1], %2, %3;"
                 ::"l"(dst), "r"(src), "r"(bytes), "l"(policy_evict_first()) : "memory");
}
__device__ __forceinline__ bool elect_one() {
    uint32_t r;
    asm volatile("{\n.reg .pred p;\nelect.sync _|p, 0xffffffff;\nselp.b32 %0, 1, 0, p;\n}" : "=r"(r));
    return r;
}
__device__ __forceinline__ void wg_fence() { asm volatile("wgmma.fence.sync.aligned;" ::: "memory"); }
__device__ __forceinline__ void wg_commit() { asm volatile("wgmma.commit_group.sync.aligned;" ::: "memory"); }
template <int N> __device__ __forceinline__ void wg_wait() { asm volatile("wgmma.wait_group.sync.aligned %0;" ::"n"(N) : "memory"); }
__device__ __forceinline__ void bar_sync(int id) { asm volatile("bar.sync %0, 256;" ::"r"(id) : "memory"); }
__device__ __forceinline__ void bar_arrive(int id) { asm volatile("bar.arrive %0, 256;" ::"r"(id) : "memory"); }
__device__ __forceinline__ float ex2(float x) { float y; asm("ex2.approx.ftz.f32 %0, %1;" : "=f"(y) : "f"(x)); return y; }
__device__ __forceinline__ uint32_t pack_bf16(float lo, float hi) {
    uint32_t r; asm("cvt.rn.bf16x2.f32 %0, %1, %2;" : "=r"(r) : "f"(hi), "f"(lo)); return r;
}
__device__ __forceinline__ void stsm4(uint32_t addr, uint32_t a, uint32_t b, uint32_t c, uint32_t d) {
    asm volatile("stmatrix.sync.aligned.m8n8.x4.shared.b16 [%0], {%1, %2, %3, %4};" ::"r"(addr), "r"(a), "r"(b), "r"(c), "r"(d) : "memory");
}
template <int N> __device__ __forceinline__ void reg_fence(float (&d)[N]) {
#pragma unroll
    for (int i = 0; i < N; i++) asm volatile("" : "+f"(d[i])::"memory");
}
#define SCHED_FENCE(x) asm volatile("{\n.reg .pred p;\nsetp.ne.s32 p, %0, 0;\n@p exit;\n}" ::"r"(x))

__device__ __forceinline__ uint64_t mk_desc(uint32_t addr, uint32_t lbo, uint32_t sbo = 1024) {
    uint32_t lo = ((addr & 0x3FFFF) >> 4) | ((lbo >> 4) << 16);
    return ((uint64_t)(0x40000000u | (sbo >> 4)) << 32) | lo;
}
#define DOFF(bytes) ((uint64_t)((bytes) >> 4))

#define ACC64 "{%0, %1, %2, %3, %4, %5, %6, %7, %8, %9, %10, %11, %12, %13, %14, %15, " \
              "%16, %17, %18, %19, %20, %21, %22, %23, %24, %25, %26, %27, %28, %29, %30, %31, " \
              "%32, %33, %34, %35, %36, %37, %38, %39, %40, %41, %42, %43, %44, %45, %46, %47, " \
              "%48, %49, %50, %51, %52, %53, %54, %55, %56, %57, %58, %59, %60, %61, %62, %63}"
#define C8(c, d, o) c(d[o]), c(d[o + 1]), c(d[o + 2]), c(d[o + 3]), c(d[o + 4]), c(d[o + 5]), c(d[o + 6]), c(d[o + 7])
#define C64(c, d) C8(c, d, 0), C8(c, d, 8), C8(c, d, 16), C8(c, d, 24), C8(c, d, 32), C8(c, d, 40), C8(c, d, 48), C8(c, d, 56)

template <int TB> __device__ __forceinline__ void mma_ss(float (&d)[64], uint64_t da, uint64_t db) {
    asm volatile("wgmma.mma_async.sync.aligned.m64n128k16.f32.bf16.bf16 " ACC64 ", %64, %65, 1, 1, 1, 0, %66;"
                 : C64("+f", d) : "l"(da), "l"(db), "n"(TB));
}
template <int TB> __device__ __forceinline__ void mma_ss_init(float (&d)[64], uint64_t da, uint64_t db) {
    asm volatile("wgmma.mma_async.sync.aligned.m64n128k16.f32.bf16.bf16 " ACC64 ", %64, %65, 0, 1, 1, 0, %66;"
                 : C64("=f", d) : "l"(da), "l"(db), "n"(TB));
}
__device__ __forceinline__ void mma_rs(float (&d)[64], const uint32_t* a, uint64_t db, int acc) {
    asm volatile("{\n.reg .pred p;\nsetp.ne.b32 p, %69, 0;\n"
                 "wgmma.mma_async.sync.aligned.m64n128k16.f32.bf16.bf16 " ACC64 ", {%64, %65, %66, %67}, %68, p, 1, 1, 1;\n}"
                 : C64("+f", d) : "r"(a[0]), "r"(a[1]), "r"(a[2]), "r"(a[3]), "l"(db), "r"(acc));
}

__device__ __forceinline__ void stage_tile(const float (&d)[64], float s0, float s1, uint32_t st_addr) {
#pragma unroll
    for (int j = 0; j < 8; j++)
        stsm4((st_addr + (j >> 2) * A_SLOT) ^ ((j & 3) * 32),
              pack_bf16(d[8 * j] * s0, d[8 * j + 1] * s0), pack_bf16(d[8 * j + 2] * s1, d[8 * j + 3] * s1),
              pack_bf16(d[8 * j + 4] * s0, d[8 * j + 5] * s0), pack_bf16(d[8 * j + 6] * s1, d[8 * j + 7] * s1));
}
__device__ __forceinline__ void stage_tile(const float (&d)[64], uint32_t st_addr) {
#pragma unroll
    for (int j = 0; j < 8; j++)
        stsm4((st_addr + (j >> 2) * A_SLOT) ^ ((j & 3) * 32), pack_bf16(d[8 * j], d[8 * j + 1]), pack_bf16(d[8 * j + 2], d[8 * j + 3]),
              pack_bf16(d[8 * j + 4], d[8 * j + 5]), pack_bf16(d[8 * j + 6], d[8 * j + 7]));
}
__device__ __forceinline__ void stage_q(const uint32_t (&p)[32], uint32_t q_addr) {
#pragma unroll
    for (int j = 0; j < 8; j++) stsm4(q_addr + (j >> 2) * A_SLOT + (j & 3) * 256, p[4 * j], p[4 * j + 1], p[4 * j + 2], p[4 * j + 3]);
}
__device__ __forceinline__ void stage_q(const float (&d)[64], uint32_t q_addr) {
#pragma unroll
    for (int j = 0; j < 8; j++)
        stsm4(q_addr + (j >> 2) * A_SLOT + (j & 3) * 256, pack_bf16(d[8 * j], d[8 * j + 1]), pack_bf16(d[8 * j + 2], d[8 * j + 3]),
              pack_bf16(d[8 * j + 4], d[8 * j + 5]), pack_bf16(d[8 * j + 6], d[8 * j + 7]));
}
__device__ __forceinline__ void stash_q(const uint32_t (&p)[32], char* dst) {
#pragma unroll
    for (int j = 0; j < 32; j++) *(uint32_t*)(dst + (j >> 4) * A_SLOT + (j & 1) * 1024 + ((j >> 1) & 7) * 128) = p[j];
}
__device__ __forceinline__ void stash_q(const float (&d)[64], char* dst) {
#pragma unroll
    for (int j = 0; j < 32; j++)
        *(uint32_t*)(dst + (j >> 4) * A_SLOT + (j & 1) * 1024 + ((j >> 1) & 7) * 128) = pack_bf16(d[2 * j], d[2 * j + 1]);
}
__device__ __forceinline__ void write_out(const float (&d)[64], uint32_t st_addr, uint32_t rows, char* out, uint32_t op, int warp, int lane) {
    stage_tile(d, st_addr);
    __syncwarp();
    char* dst = out + ((op_g(op) & 7) * SQ + warp * 16) * (4 * DM) + (op_g(op) >> 3) * (2 * DM) + (op_h(op) & 3) * 512 + (op_takeover(op) ? 0 : 256);
#pragma unroll
    for (int j = 0; j < 8; j++) {
        const int r = (j & 3) * 4 + (lane >> 3);
        uint4 v;
        asm volatile("ld.shared.v4.u32 {%0, %1, %2, %3}, [%4];" : "=r"(v.x), "=r"(v.y), "=r"(v.z), "=r"(v.w)
                     : "r"(rows + (j >> 2) * A_SLOT + r * 128 + (((lane ^ r) & 7) << 4)) : "memory");
        *(uint4*)(dst + r * (4 * DM) + (j >> 2) * 128 + (lane & 7) * 16) = v;
    }
}
__device__ __forceinline__ void publish_tile(uint32_t bar, int lane) {
    asm volatile("fence.proxy.async.shared::cta;" ::: "memory");
    __syncwarp();
    if (lane == 0) mbar_arrive(bar);
}

template <bool INIT>
__device__ __forceinline__ void gemm_step(float (&c)[64], uint64_t a, uint64_t b) {
    if (INIT) mma_ss_init<1>(c, a, b); else mma_ss<1>(c, a, b);
#pragma unroll
    for (int kk = 1; kk < 4; kk++) mma_ss<1>(c, a + DOFF(kk * 32), b + DOFF(kk * 4096));
}

template <bool INIT>
__device__ __forceinline__ void gemm_phase1(float (&c0)[64], uint32_t sb, int wg, int lane, uint32_t& it, int nk) {
    const uint64_t a0 = mk_desc(sb + OFF_A + wg * 8192, 16), b0 = mk_desc(sb + OFF_B, 1024, 2048);
    if (INIT) {
        mbar_wait(sb + BAR_FULL, 0);
        wg_fence();
        gemm_step<true>(c0, a0, b0);
        wg_commit();
        wg_wait<0>();
        if (lane == 0) mbar_arrive(sb + BAR_EMPTY);
        it++;
    }
#pragma unroll 1
    for (int ks = INIT; ks < nk; ks++) {
        const uint32_t s = it & 3;
        mbar_wait(sb + BAR_FULL + s * 8, (it >> 2) & 1);
        wg_fence();
        gemm_step<false>(c0, a0 + s * (A_SLOT >> 4), b0 + s * (B_SLOT >> 4));
        wg_commit();
        wg_wait<0>();
        if (lane == 0) mbar_arrive(sb + BAR_EMPTY + s * 8);
        it++;
    }
    reg_fence(c0);
}

__device__ __forceinline__ void gemm_phase2(float (&c0)[64], float (&c1)[64], const uint32_t (&p)[32], uint32_t sb, int wg, int lane,
                                            uint32_t& it, int nk, uint32_t pend, uint32_t op, uint32_t staged) {
    const uint64_t a0 = mk_desc(sb + OFF_A + wg * 8192, 16), b0 = mk_desc(sb + OFF_B, 1024, 2048);
    char* const stash = (char*)g_o + (threadIdx.x >> 5) * 2048 + lane * 4;
    const uint32_t ph0 = (it >> 2) & 1;
    mbar_wait(sb + BAR_FULL, ph0);
    wg_fence();
    gemm_step<true>(c0, a0, b0);
    wg_commit();
    mbar_wait(sb + BAR_FULL + 8, ph0);
    wg_fence();
    gemm_step<false>(c0, a0 + DOFF(A_SLOT), b0 + DOFF(B_SLOT));
    wg_commit();
    if (pend) {
        stash_q(p, stash + (size_t)pend * 2 * A_SLOT);
        __syncwarp();
        if (lane == 0) mbar_arrive(staged);
    }
    wg_fence();
    gemm_step<true>(c1, a0, b0 + DOFF(16384));
    wg_commit();
    gemm_step<false>(c1, a0 + DOFF(A_SLOT), b0 + DOFF(B_SLOT + 16384));
    wg_commit();
    wg_wait<1>();
    if (lane == 0) mbar_arrive(sb + BAR_EMPTY);
    wg_wait<0>();
    if (lane == 0) mbar_arrive(sb + BAR_EMPTY + 8);
    it += 2;
#pragma unroll 1
    for (int ks = 2; ks < nk - 2; ks++) {
        const uint32_t s = it & 3;
        const uint64_t a = a0 + s * (A_SLOT >> 4), b = b0 + s * (B_SLOT >> 4);
        mbar_wait(sb + BAR_FULL + s * 8, (it >> 2) & 1);
        wg_fence();
#pragma unroll
        for (int kk = 0; kk < 4; kk++) {
            mma_ss<1>(c0, a + DOFF(kk * 32), b + DOFF(kk * 4096));
            mma_ss<1>(c1, a + DOFF(kk * 32), b + DOFF(16384 + kk * 4096));
        }
        wg_commit();
        wg_wait<0>();
        if (lane == 0) mbar_arrive(sb + BAR_EMPTY + s * 8);
        it++;
    }
    const uint32_t ph1 = (it >> 2) & 1, s1 = it & 2;
    const uint64_t a1 = a0 + s1 * (A_SLOT >> 4), b1 = b0 + s1 * (B_SLOT >> 4);
    mbar_wait(sb + BAR_FULL + s1 * 8, ph1);
    wg_fence();
    gemm_step<false>(c0, a1, b1);
    wg_commit();
    mbar_wait(sb + BAR_FULL + s1 * 8 + 8, ph1);
    wg_fence();
    gemm_step<false>(c0, a1 + DOFF(A_SLOT), b1 + DOFF(B_SLOT));
    wg_commit();
    gemm_step<false>(c1, a1, b1 + DOFF(16384));
    gemm_step<false>(c1, a1 + DOFF(A_SLOT), b1 + DOFF(B_SLOT + 16384));
    wg_commit();
    wg_wait<1>();
    reg_fence(c0);
    if (op_type(op) == OP_OT) {
        float4* dst = g_park + op_tile(op) * (12 * 16 * 32) + (threadIdx.x >> 5) * (16 * 32) + lane;
#pragma unroll
        for (int j = 0; j < 16; j++) dst[j * 32] = make_float4(c0[4 * j], c0[4 * j + 1], c0[4 * j + 2], c0[4 * j + 3]);
        __syncwarp();
        if (lane == 0) mbar_arrive(staged);
    } else if (op & Q_STASH) {
        stash_q(c0, stash + (size_t)op_head(op) * 2 * A_SLOT);
    }
    wg_wait<0>();
    reg_fence(c1);
    if (lane == 0) { mbar_arrive(sb + BAR_EMPTY + s1 * 8); mbar_arrive(sb + BAR_EMPTY + s1 * 8 + 8); }
    it += 2;
}

__device__ __forceinline__ void qk_issue(float (&s)[64], uint64_t qa, uint64_t kb) {
    mma_ss_init<0>(s, qa, kb);
#pragma unroll
    for (int kk = 1; kk < 8; kk++)
        mma_ss<0>(s, qa + DOFF((kk >> 2) * A_SLOT + (kk & 3) * 256), kb + DOFF((kk >> 2) * 1024 + (kk & 3) * 32));
}

__device__ __forceinline__ int imax3(float a, float b, float c) {
    return __vimax3_s32(__float_as_int(a), __float_as_int(b), __float_as_int(c));
}

__device__ __forceinline__ void softmax_block(float (&s)[64], uint32_t (&p)[32], float (&o)[64], float& n0, float& n1,
                                              float& l0, float& l1, int never, bool first) {
    constexpr float C = 0.08838834764831845f * 1.4426950408889634f;
    int i0 = imax3(s[0], s[1], s[4]), i1 = imax3(s[2], s[3], s[6]);
    int j0 = imax3(s[5], s[8], s[9]), j1 = imax3(s[7], s[10], s[11]);
#pragma unroll
    for (int j = 3; j < 15; j += 2) {
        i0 = imax3(__int_as_float(i0), s[4 * j], s[4 * j + 1]);
        i1 = imax3(__int_as_float(i1), s[4 * j + 2], s[4 * j + 3]);
        j0 = imax3(__int_as_float(j0), s[4 * j + 4], s[4 * j + 5]);
        j1 = imax3(__int_as_float(j1), s[4 * j + 6], s[4 * j + 7]);
    }
    i0 = imax3(__int_as_float(i0), s[60], s[61]);
    i1 = imax3(__int_as_float(i1), s[62], s[63]);
    i0 = imax3(__int_as_float(i0), __int_as_float(j0), 0.f);
    i1 = imax3(__int_as_float(i1), __int_as_float(j1), 0.f);
    if (__any_sync(0xffffffffu, !(fmaf(__int_as_float(i0), C, n0) <= 8.f && fmaf(__int_as_float(i1), C, n1) <= 8.f))) {
        i0 = max(i0, __shfl_xor_sync(0xffffffffu, i0, 1));
        i1 = max(i1, __shfl_xor_sync(0xffffffffu, i1, 1));
        i0 = max(i0, __shfl_xor_sync(0xffffffffu, i0, 2));
        i1 = max(i1, __shfl_xor_sync(0xffffffffu, i1, 2));
        float x0 = __int_as_float(i0), x1 = __int_as_float(i1);
        if (__any_sync(0xffffffffu, i0 == 0 || i1 == 0)) {
            x0 = x1 = -INFINITY;
#pragma unroll
            for (int j = 0; j < 16; j++) {
                x0 = fmaxf(x0, fmaxf(s[4 * j], s[4 * j + 1]));
                x1 = fmaxf(x1, fmaxf(s[4 * j + 2], s[4 * j + 3]));
            }
            x0 = fmaxf(x0, __shfl_xor_sync(0xffffffffu, x0, 1));
            x1 = fmaxf(x1, __shfl_xor_sync(0xffffffffu, x1, 1));
            x0 = fmaxf(x0, __shfl_xor_sync(0xffffffffu, x0, 2));
            x1 = fmaxf(x1, __shfl_xor_sync(0xffffffffu, x1, 2));
        }
        x0 = fminf(n0, -x0 * C);
        x1 = fminf(n1, -x1 * C);
        if (!first) {
            const float r0 = ex2(x0 - n0), r1 = ex2(x1 - n1);
            l0 *= r0;
            l1 *= r1;
#pragma unroll
            for (int j = 0; j < 32; j++) { o[2 * j] *= (j & 1) ? r1 : r0; o[2 * j + 1] *= (j & 1) ? r1 : r0; }
        }
        n0 = x0;
        n1 = x1;
    }
    float t0 = l0, t1 = l1, u0 = 0.f, u1 = 0.f;
    constexpr int LAG = 2;
#pragma unroll
    for (int c = -1; c < 32 + LAG; c++) {
        if (c >= 0 && c < 32) { s[2 * c] = ex2(s[2 * c]); s[2 * c + 1] = ex2(s[2 * c + 1]); }
        if (c + 1 < 32) {
            const int j = c + 1;
            s[2 * j] = fmaf(s[2 * j], C, (j & 1) ? n1 : n0);
            s[2 * j + 1] = fmaf(s[2 * j + 1], C, (j & 1) ? n1 : n0);
        }
        if (c >= LAG) {
            const int j = c - LAG;
            if (j & 1) { t1 += s[2 * j]; if (j == 1) u1 = s[3]; else u1 += s[2 * j + 1]; }
            else { t0 += s[2 * j]; if (j == 0) u0 = s[1]; else u0 += s[2 * j + 1]; }
            p[j] = pack_bf16(s[2 * j], s[2 * j + 1]);
        }
        if (c >= 0 && c < 31) {
#pragma unroll
            for (int i = 0; i < 64; i++) if (i >= 2 * (c - LAG + 1)) asm volatile("" : "+f"(s[i]));
#pragma unroll
            for (int i = 0; i < 32; i++) if (i < c - LAG + 1) asm volatile("" : "+r"(p[i]));
            asm volatile("" : "+f"(t0), "+f"(t1), "+f"(u0), "+f"(u1));
            SCHED_FENCE(never);
        }
    }
    l0 = t0 + u0;
    l1 = t1 + u1;
}

__device__ __forceinline__ void attn_epilogue(float (&o)[64], float l0, float l1, uint32_t st_addr) {
    l0 += __shfl_xor_sync(0xffffffffu, l0, 1);
    l1 += __shfl_xor_sync(0xffffffffu, l1, 1);
    l0 += __shfl_xor_sync(0xffffffffu, l0, 2);
    l1 += __shfl_xor_sync(0xffffffffu, l1, 2);
    stage_tile(o, __fdividef(1.f, l0), __fdividef(1.f, l1), st_addr);
}

__global__ void __launch_bounds__(NTHREADS, 1) mha2_kernel(const __grid_constant__ Params prm) {
    extern __shared__ __align__(1024) char smem_raw[];
    const uint32_t sb = smem_u32(smem_raw);
    const int tid = threadIdx.x, lane = tid & 31;
    const int warp = __shfl_sync(0xffffffffu, tid >> 5, 0);
    const int cta = blockIdx.x;

    if (warp == 12 && elect_one()) {
        uint32_t role, nsm;
        asm volatile("mov.u32 %0, %smid;" : "=r"(role));
        asm volatile("mov.u32 %0, %nsmid;" : "=r"(nsm));
        if (nsm != NCTA) role = cta;
        for (int i = 0; i < 4; i++) mbar_init(sb + BAR_FULL + 8 * i, 1);
        asm volatile("fence.mbarrier_init.release.cluster;" ::: "memory");
        const uint32_t op = prm.ops[role][0], br = op_g(op) >> 3;
        const bool two = op & Q_TWO;
#pragma unroll 1
        for (int s = 0; s < 4; s++) {
            mbar_expect_tx(sb + BAR_FULL + s * 8, two ? A_SLOT + B_SLOT : A_SLOT + B_SLOT / 2);
            tma_2d(sb + OFF_A + s * A_SLOT, &prm.x[br], s * 64, (op_g(op) & 7) * SQ, sb + BAR_FULL + s * 8);
            tma_w(sb + OFF_B + s * B_SLOT, &prm.wq[br], s * 64, op_h(op) * 2, sb + BAR_FULL + s * 8);
            if (two) tma_w(sb + OFF_B + s * B_SLOT + 16384, &prm.wq[br], s * 64, op_h(op) * 2 + 2, sb + BAR_FULL + s * 8);
        }
#pragma unroll
        for (int j = 0; j < MAXOPS / 2; j++)
            asm volatile("st.shared.u32 [%0], %1;" ::"r"(sb + OFF_OPS + 4 * j), "r"(((const uint32_t*)prm.ops[role])[j]) : "memory");
        asm volatile("prefetch.tensormap [%0];" ::"l"(&prm.k[br]) : "memory");
        asm volatile("prefetch.tensormap [%0];" ::"l"(&prm.v[br]) : "memory");
    }
    if (tid == 0) {
        for (int i = 0; i < 4; i++) mbar_init(sb + BAR_EMPTY + 8 * i, 12);
        for (int i = 0; i < 2; i++) mbar_init(sb + BAR_QFREE + 8 * i, 3);
        for (int i = 0; i < 3; i++) {
            mbar_init(sb + BAR_STAGED + 8 * i, 4);
            mbar_init(sb + BAR_QREADY + 8 * i, 1);
        }
        asm volatile("fence.mbarrier_init.release.cluster;" ::: "memory");
    }
    __syncthreads();
    auto get_op = [&](int i) {
        uint32_t v;
        asm volatile("ld.shared.u16 %0, [%1];" : "=r"(v) : "r"(sb + OFF_OPS + 2 * i));
        return __shfl_sync(0xffffffffu, v, 0);
    };

    if (warp >= 12) {
        asm volatile("setmaxnreg.dec.sync.aligned.u32 32;");
        const unsigned epoch0 = g_epoch[cta];
        if (warp == 12) {
            uint32_t it = 4;
            bool after_att = false;
#pragma unroll 1
            for (int i = 0;; i++) {
                const uint32_t op = get_op(i);
                const uint32_t ty = op_type(op), g = op_g(op), h = op_h(op), br = g >> 3;
                if (ty == OP_END) break;
                if (ty == OP_AT) {
                    const int row0 = ((g & 7) * NH + h) * SK;
#pragma unroll 1
                    for (int t = 0; t < 16; t++, it++) {
                        const uint32_t s = it & 3;
                        mbar_wait_sleep(sb + BAR_EMPTY + s * 8, ((it >> 2) & 1) ^ 1);
                        if (it == 16 && h < 4) {
                            const uint32_t c0 = clock();
                            while ((uint32_t)clock() - c0 < h * STAG) __nanosleep(50);
                        }
                        if (elect_one()) {
                            mbar_expect_tx(sb + BAR_FULL + s * 8, B_SLOT);
                            tma_4d_stream(sb + OFF_B + s * B_SLOT, (t & 1) ? &prm.v[br] : &prm.k[br], (row0 + (t >> 1) * 128) / 8,
                                          sb + BAR_FULL + s * 8);
                        }
                    }
                    after_att = true;
                } else if (ty == OP_Q) {
                    const bool two = op & Q_TWO;
#pragma unroll 1
                    for (int ks = it & 15; ks < 16; ks++, it++) {
                        const uint32_t s = it & 3;
                        if (after_att && (ks == 0 || ks == 2)) mbar_wait_sleep(sb + BAR_QFREE + ks * 4, 0);
                        mbar_wait_sleep(sb + BAR_EMPTY + s * 8, ((it >> 2) & 1) ^ 1);
                        if (elect_one()) {
                            mbar_expect_tx(sb + BAR_FULL + s * 8, two ? A_SLOT + B_SLOT : A_SLOT + B_SLOT / 2);
                            tma_2d(sb + OFF_A + s * A_SLOT, &prm.x[br], ks * 64, (g & 7) * SQ, sb + BAR_FULL + s * 8);
                            tma_w(sb + OFF_B + s * B_SLOT, &prm.wq[br], ks * 64, h * 2, sb + BAR_FULL + s * 8);
                            if (two) tma_w(sb + OFF_B + s * B_SLOT + 16384, &prm.wq[br], ks * 64, h * 2 + 2, sb + BAR_FULL + s * 8);
                        }
                    }
                    after_att = false;
                } else {
                    unsigned epoch3;
                    asm volatile("mad.lo.u32 %0, %1, 3, 3;" : "=r"(epoch3) : "r"(epoch0));
                    const char* osrc = (const char*)g_o + (size_t)g * NH * 2 * A_SLOT;
                    const int k1 = op_k1(op), k0 = op_takeover(op) ? k1 : 0, col = (h & 3) * 4;
                    const bool own = k0 >= 48;
                    const uint32_t hown = 28 + (h & 3);
                    uint32_t ready = 0;
#pragma unroll 1
                    for (int ks = k0; ks < 64; ks++, it++) {
                        const uint32_t s = it & 3;
                        const bool have_a = own && ks < k0 + 2;
                        uint32_t hk = ks >> 1;
                        if (own && hk <= hown) hk = have_a ? hown : hk - 1;
                        const int kk = hk * 2 + (ks & 1);
                        if (k0 && ks == 60) flag_wait(g_pflag + op_tile(op), epoch3);
                        mbar_wait_sleep(sb + BAR_EMPTY + s * 8, ((it >> 2) & 1) ^ 1);
                        if (elect_one()) {
                            mbar_expect_tx(sb + BAR_FULL + s * 8, (have_a ? 0 : A_SLOT) + (ks < k1 ? B_SLOT : B_SLOT / 2));
                            tma_w(sb + OFF_B + s * B_SLOT, &prm.wo[br], kk * 64, (ks < k1 || k0) ? col : col + 2, sb + BAR_FULL + s * 8);
                            if (ks < k1) tma_w(sb + OFF_B + s * B_SLOT + 16384, &prm.wo[br], kk * 64, col + 2, sb + BAR_FULL + s * 8);
                            if (ks >= 40 && ks < 56 && !k0) tma_prefetch_w(&prm.wo[br], (36 + (ks >> 1)) * 64, col + (ks & 1) * 2);
                        }
                        if (have_a) continue;
                        if (!((ready >> hk) & 1)) {
                            ready = flag_wait_any(g_flag + g * NH + lane, epoch3, 1u << hk);
                            __syncwarp();
                            asm volatile("fence.proxy.async.global;" ::: "memory");
                        }
                        if (after_att && ks == k0 + (own ? 4 : 0)) mbar_wait_sleep(sb + BAR_QFREE, 0);
                        if (after_att && ks == k0 + 2) mbar_wait_sleep(sb + BAR_QFREE + 8, 0);
                        if (elect_one()) bulk_load(sb + OFF_A + s * A_SLOT, osrc + (size_t)kk * A_SLOT, A_SLOT, sb + BAR_FULL + s * 8);
                    }
                }
            }
        } else {
            const int w = warp - 13;
            const unsigned epoch = epoch0 + 1;
#pragma unroll 1
            for (int i = 0;; i++) {
                const uint32_t op = get_op(i);
                const uint32_t ty = op_type(op);
                if (ty == OP_END || (ty == OP_OT && op_takeover(op))) break;
                const uint32_t n1 = get_op(i + 1);
                const bool more = op_type(n1) == OP_AT && !(n1 & AT_LAST);
                mbar_wait_sleep(sb + BAR_STAGED + w * 8, i & 1);
                if (lane == 0) {
                    if (ty == OP_Q) {
                        if (op & Q_STASH) {
                            __threadfence();
                            asm volatile("st.relaxed.gpu.global.u32 [%0], %1;" ::"l"(g_qflag + op_head(op) * 4 + w), "r"(epoch) : "memory");
                            if (op & Q_STASH1) asm volatile("st.relaxed.gpu.global.u32 [%0], %1;" ::"l"(g_qflag + op_head(op) * 4 + 4 + w), "r"(epoch) : "memory");
                            else mbar_arrive(sb + BAR_QFREE);
                        }
                    } else if (ty == OP_AT) {
                        char* dst = (char*)g_o + (size_t)op_head(op) * 2 * A_SLOT + w * 8192;
                        const uint32_t src = sb + OFF_A + ((op & AT_BUF1) ? 2 * A_SLOT : 0) + w * 8192;
                        bulk_store_stream(dst, src, 8192);
                        bulk_store_stream(dst + A_SLOT, src + A_SLOT, 8192);
                        asm volatile("cp.async.bulk.commit_group;" ::: "memory");
                        asm volatile("cp.async.bulk.wait_group 0;" ::: "memory");
                        if (!more) mbar_arrive(sb + BAR_QFREE + ((op & AT_BUF1) ? 8 : 0));
                        asm volatile("red.release.gpu.global.add.u32 [%0], 1;" ::"l"(g_flag + op_head(op)) : "memory");
                    } else {
                        asm volatile("red.release.gpu.global.add.u32 [%0], 1;" ::"l"(g_pflag + op_tile(op)) : "memory");
                    }
                }
                __syncwarp();
                if (!more) continue;
                const uint32_t n2 = get_op(i + 2);
                if (!(n2 & AT_STASH)) continue;
                if (lane == 0) {
                    flag_wait(g_qflag + op_head(n2) * 4 + w, epoch);
                    asm volatile("fence.proxy.async.global;" ::: "memory");
                    const uint32_t buf = sb + OFF_A + ((n2 & AT_BUF1) ? 2 * A_SLOT : 0) + w * 8192;
                    const char* src = (const char*)g_o + (size_t)op_head(n2) * 2 * A_SLOT + w * 8192;
                    mbar_expect_tx(sb + BAR_QREADY + w * 8, 16384);
                    bulk_load_stream(buf, src, 8192, sb + BAR_QREADY + w * 8);
                    bulk_load_stream(buf + A_SLOT, src + A_SLOT, 8192, sb + BAR_QREADY + w * 8);
                }
                __syncwarp();
            }
        }
        asm volatile("bar.sync 4, 128;" ::: "memory");
        if (tid == 384) g_epoch[cta] = epoch0 + 1;

    } else {
        asm volatile("setmaxnreg.inc.sync.aligned.u32 160;");
        const int wg = warp >> 2;
        const int my_bar = 1 + wg, next_bar = wg == 2 ? 1 : 2 + wg;
        const uint32_t qa0 = sb + OFF_A + wg * 8192;
        const uint32_t st_addr = qa0 + ((warp & 3) * 16 + (lane & 15)) * 128 + (((lane >> 4) ^ (lane & 7)) << 4);
#define Q_ADDR (sb + OFF_A + warp * 2048 + ((lane >> 3) & 1) * 1024 + (lane >> 4) * 128 + (lane & 7) * 16)
        const uint32_t staged = sb + BAR_STAGED + wg * 8;
        const uint64_t qd0 = mk_desc(qa0, 128) & ~(3ull << 62);
        const uint64_t kd0 = mk_desc(sb + OFF_B, 16, 2048), vd0 = mk_desc(sb + OFF_B, 1024, 2048);
        float o[64], s[64];
        uint32_t p[32];
        uint32_t it = 0, pend = 0;
        int i = 0;
#pragma unroll
        for (int j = 0; j < 32; j++) p[j] = 0;
#pragma unroll 1
        for (;;) {
            const uint32_t op = get_op(i);
            if (op_type(op) == OP_END) break;
            if (op_type(op) != OP_AT) {
                if (op_type(op) == OP_Q && !(op & Q_TWO)) {
                    gemm_phase1<true>(o, sb, wg, lane, it, 16);
                    stage_q(o, Q_ADDR);
                    publish_tile(staged, lane);
                } else if (op_type(op) == OP_OT && op_takeover(op)) {
#pragma unroll
                    for (int j = 0; j < 64; j++) s[j] = 0.f;
                    reg_fence(s);
                    asm volatile("bar.sync %0, 128;" ::"r"(5 + wg) : "memory");
                    gemm_phase1<false>(s, sb, wg, lane, it, 60 - op_k1(op));
                    const float4* src = g_park + op_tile(op) * (12 * 16 * 32) + (tid >> 5) * (16 * 32) + lane;
                    const uint64_t a0 = mk_desc(qa0, 16), b0 = mk_desc(sb + OFF_B, 1024, 2048);
#pragma unroll
                    for (int ks = 0; ks < 4; ks++) {
                        const uint32_t sl = it & 3;
                        mbar_wait(sb + BAR_FULL + sl * 8, (it >> 2) & 1);
                        wg_fence();
                        gemm_step<false>(s, a0 + sl * (A_SLOT >> 4), b0 + sl * (B_SLOT >> 4));
                        wg_commit();
                        it++;
#pragma unroll
                        for (int j = 4 * ks; j < 4 * ks + 4; j++) {
                            const float4 v = __ldcg(src + j * 32);
                            o[4 * j] = v.x; o[4 * j + 1] = v.y; o[4 * j + 2] = v.z; o[4 * j + 3] = v.w;
                        }
                    }
                    wg_wait<0>();
                    reg_fence(s);
#pragma unroll
                    for (int j = 0; j < 64; j++) s[j] += o[j];
                    write_out(s, st_addr, sb + OFF_A + warp * 2048, prm.out, op, warp, lane);
                    break;
                } else {
                    gemm_phase2(o, s, p, sb, wg, lane, it, op_type(op) == OP_Q ? 16 : op_k1(op), pend, op, staged);
                    if (op_type(op) == OP_OT) {
                        gemm_phase1<false>(s, sb, wg, lane, it, 64 - op_k1(op));
                        write_out(s, st_addr, sb + OFF_A + warp * 2048, prm.out, op, warp, lane);
                        break;
                    }
#pragma unroll
                    for (int j = 0; j < 32; j++) p[j] = pack_bf16(s[2 * j], s[2 * j + 1]);
                    pend = 0;
                    if (op & Q_STASH1) {
                        pend = op_head(op) + 1;
                    } else {
                        if (!(op & Q_STASH)) stage_q(o, Q_ADDR);
                        stage_q(p, Q_ADDR + 2 * A_SLOT);
                        publish_tile(staged, lane);
                    }
                }
                i++;
                continue;
            }
            float n0 = INFINITY, n1 = INFINITY, l0 = 0.f, l1 = 0.f;
            int t = (op & AT_BUF1) ? 8 : 0, tend = (t + 8) | ((get_op(i + 1) & AT_STASH) ? 8 << 8 : 16 << 8);
            while (!(get_op(i++) & AT_LAST)) tend += 8;
            if (wg == 2) bar_arrive(1);
            mbar_wait(sb + BAR_FULL, (it >> 2) & 1);
            bar_sync(my_bar);
            wg_fence();
            qk_issue(s, qd0 + t * (2 * A_SLOT / 128), kd0);
            wg_commit();
            bar_arrive(next_bar);
            wg_wait<0>();
            reg_fence(s);
            if (lane == 0) mbar_arrive(sb + BAR_EMPTY);
            it++;
            softmax_block(s, p, o, n0, n1, l0, l1, prm.never, true);
#pragma unroll 1
            for (t++; t != (tend & 255); t++) {
                const bool flip = (t & 7) == 0;
                if (flip && t >= (tend >> 8)) mbar_wait(sb + BAR_QREADY + wg * 8, ((t - (tend >> 8)) >> 3) & 1);
                const uint32_t sv = it & 3, sk = (it + 1) & 3;
                const uint64_t vb = vd0 + sv * (B_SLOT >> 4), kb = kd0 + sk * (B_SLOT >> 4), qd = qd0 + (t & 8) * (2 * A_SLOT / 128);
                mbar_wait(sb + BAR_FULL + sv * 8, (it >> 2) & 1);
                bar_sync(my_bar);
                wg_fence();
                mma_rs(o, p, vb, (t & 7) != 1);
#pragma unroll
                for (int kk = 1; kk < 7; kk++) mma_rs(o, p + 4 * kk, vb + DOFF(kk * 4096), 1);
                wg_commit();
                mma_rs(o, p + 28, vb + DOFF(7 * 4096), 1);
                wg_commit();
                mbar_wait(sb + BAR_FULL + sk * 8, ((it + 1) >> 2) & 1);
                wg_wait<1>();
                wg_fence();
                qk_issue(s, qd, kb);
                wg_commit();
                bar_arrive(next_bar);
                wg_wait<1>();
                reg_fence(o);
                if (lane == 0) mbar_arrive(sb + BAR_EMPTY + sv * 8);
                if (flip) {
                    attn_epilogue(o, l0, l1, st_addr + (~t & 8) * (2 * A_SLOT / 8));
                    publish_tile(staged, lane);
                    n0 = n1 = INFINITY;
                    l0 = l1 = 0.f;
                }
                wg_wait<0>();
                reg_fence(s);
                if (lane == 0) mbar_arrive(sb + BAR_EMPTY + sk * 8);
                it += 2;
                softmax_block(s, p, o, n0, n1, l0, l1, prm.never, flip);
            }
            {
                const uint64_t vb = vd0 + DOFF(3 * B_SLOT);
                mbar_wait(sb + BAR_FULL + 3 * 8, (it >> 2) & 1);
                bar_sync(my_bar);
                wg_fence();
#pragma unroll
                for (int kk = 0; kk < 8; kk++) mma_rs(o, p + 4 * kk, vb + DOFF(kk * 4096), 1);
                wg_commit();
                if (wg != 2) bar_arrive(next_bar);
                wg_wait<0>();
                reg_fence(o);
                if (lane == 0) mbar_arrive(sb + BAR_EMPTY + 3 * 8);
                it++;
                attn_epilogue(o, l0, l1, st_addr + (~t & 8) * (2 * A_SLOT / 8));
                publish_tile(staged, lane);
            }
        }
    }
}

void build_schedule(uint16_t (*ops)[MAXOPS]) {
    for (int c = 0; c < NCTA; c++) for (int j = 0; j < MAXOPS; j++) ops[c][j] = OP_END;
    auto mk = [](uint32_t ty, int g, int h, uint32_t fl) { return (uint16_t)(ty | (g << 2) | (h << 6) | fl); };
    int sm_of[128], cnt[8] = {0, 0, 0, 0, 0, 0, 0, 0};
    for (int sm = 0; sm < NCTA; sm++) {
        if (sm >= 120 && sm < 124) continue;
        const int gpc = sm < 64 ? (sm & 15) >> 1 : sm < 120 ? 1 + (sm - 64) % 14 / 2 : 0;
        sm_of[((0x73216540u >> (4 * gpc)) & 7) * 16 + cnt[gpc]++] = sm;
    }
    auto ncta = [&](int g, int j) { return sm_of[(((g & 8) >> 1) | (g & 3)) * 16 + j * 4 + ((g >> 2) & 1)]; };
    auto mcta = [&](int g, int j) { return sm_of[(((g & 8) >> 1) | (g & 3)) * 16 + j * 4 + 2 + ((g >> 2) & 1)]; };
    static const char* const plan[4][4] = {{"paas", "ssss", "ssss", "sssx"}, {"mass", "ssma", "ssss", "ssss"},
                                           {"mass", "ssma", "ssss", "ssss"}, {"spaa", "sssss", "paas", "ssss"}};
    for (int g = 0; g < 16; g++) {
        const int q = g & 3;
        uint16_t* oe = ops[120 + (g >> 2)];
        int st[28], ns = 0, h = 4;
        for (int sl = 0; sl < 5; sl++) {
            for (int j = 0; j < 4; j++) {
                uint16_t* o = ops[mcta(g, j)];
                const char c = plan[q][j][sl];
                if (c == 's') { o[sl] = mk(OP_Q, g, h, Q_TWO | Q_STASH | Q_STASH1); st[ns++] = h; st[ns++] = h + 1; }
                if (c == 'm') { o[sl] = mk(OP_Q, g, h, Q_TWO | Q_STASH); o[sl + 1] = mk(OP_AT, g, h + 1, AT_BUF1 | AT_LAST); st[ns++] = h; }
                if (c == 'p') { o[sl] = mk(OP_Q, g, h, Q_TWO); o[sl + 1] = mk(OP_AT, g, h, 0); o[sl + 2] = mk(OP_AT, g, h + 1, AT_BUF1 | AT_LAST); }
                if (c == 'x') o[sl] = mk(OP_Q, g + 3, 28, Q_TWO | Q_STASH | Q_STASH1);
                if (c == 's' || c == 'm' || c == 'p') h += 2;
                if (q == 3 && h == 28) { st[ns++] = h; st[ns++] = h + 1; h += 2; }
            }
            if (q == 0 && sl == 0) {
                oe[0] = mk(OP_Q, g, h, Q_TWO);
                oe[1] = mk(OP_AT, g, h, 0);
                oe[2] = mk(OP_AT, g, h + 1, AT_BUF1);
                h += 2;
            }
        }
        const int pos0 = q == 1 ? 2 : q == 2 ? 4 : 0, pos1 = q == 1 ? 3 : q == 2 ? 6 : 0;
        int k = 0;
        for (int w = 0; w < 7; w++) {
            if (w && pos0 == w) oe[2 * q + 1] = mk(OP_AT, g, st[k++], AT_STASH);
            if (w && pos1 == w) oe[2 * q + 2] = mk(OP_AT, g, st[k++], AT_STASH | AT_BUF1 | (q == 2 ? AT_LAST : 0));
            for (int j = 0; j < 4; j++) {
                uint16_t* o = ops[ncta(g, j)];
                if (w == 0) { o[0] = mk(OP_Q, g, j, 0); o[1] = mk(OP_AT, g, j, 0); }
                else o[w + 1] = mk(OP_AT, g, st[k++], AT_STASH | ((w & 1) ? AT_BUF1 : 0) | (w == 6 ? AT_LAST : 0));
            }
        }
        for (int j = 0; j < 4; j++) {
            if (plan[q][j][4]) {
                ops[mcta(g, j)][5] = mk(OP_OT, g, j, (K1E / 2) << 11);
                oe[7] = mk(OP_OT, g, 4 | j, (K1E / 2) << 11);
            } else {
                ops[mcta(g, j)][4] = mk(OP_OT, g, j, (K1N / 2) << 11);
                ops[ncta(g, j)][8] = mk(OP_OT, g, 4 | j, (K1N / 2) << 11);
            }
        }
    }
}

typedef CUresult (*EncodeFn)(CUtensorMap*, CUtensorMapDataType, cuuint32_t, void*, const cuuint64_t*, const cuuint64_t*,
                             const cuuint32_t*, const cuuint32_t*, CUtensorMapInterleave, CUtensorMapSwizzle,
                             CUtensorMapL2promotion, CUtensorMapFloatOOBfill);

void encode(EncodeFn fn, CUtensorMap* m, void* ptr, int rank, const cuuint64_t* dims, const cuuint64_t* strides, const cuuint32_t* box) {
    const cuuint32_t es[4] = {1, 1, 1, 1};
    fn(m, CU_TENSOR_MAP_DATA_TYPE_BFLOAT16, rank, ptr, dims, strides, box, es, CU_TENSOR_MAP_INTERLEAVE_NONE,
       CU_TENSOR_MAP_SWIZZLE_128B, CU_TENSOR_MAP_L2_PROMOTION_NONE, CU_TENSOR_MAP_FLOAT_OOB_FILL_NONE);
}

}

extern "C" void kernel_launch(void* const* d_in, const int* in_sizes, int n_in, void* d_out, int out_size) {
    static EncodeFn fn = nullptr;
    if (!fn) {
        cudaDriverEntryPointQueryResult qr;
        void* p = nullptr;
        cudaGetDriverEntryPoint("cuTensorMapEncodeTiled", &p, cudaEnableDefault, &qr);
        fn = (EncodeFn)p;
        cudaFuncSetAttribute(mha2_kernel, cudaFuncAttributeMaxDynamicSharedMemorySize, SMEM_BYTES);
    }
    Params prm;
    for (int br = 0; br < 2; br++) {
        void* x = d_in[5 * br + 0];
        void* k = d_in[5 * br + 1];
        void* v = d_in[5 * br + 2];
        void* wq = d_in[5 * br + 3];
        void* wo = d_in[5 * br + 4];
        {
            cuuint64_t dims[2] = {DM, NB * SQ}, st[1] = {DM * 2};
            cuuint32_t box[2] = {64, SQ};
            encode(fn, &prm.x[br], x, 2, dims, st, box);
        }
        {
            cuuint64_t dims[4] = {64, 8, NH * DH / 64, DM / 8}, st[3] = {NH * DH * 2, 128, 8 * NH * DH * 2};
            cuuint32_t box[4] = {64, 8, 2, 8};
            encode(fn, &prm.wq[br], wq, 4, dims, st, box);
        }
        {
            cuuint64_t dims[4] = {64, 8, 2, (cuuint64_t)NB * NH * SK / 8}, st[3] = {DH * 2, 128, 8 * DH * 2};
            cuuint32_t box[4] = {64, 8, 2, 16};
            encode(fn, &prm.k[br], k, 4, dims, st, box);
            encode(fn, &prm.v[br], v, 4, dims, st, box);
        }
        {
            cuuint64_t dims[4] = {64, 8, DM / 64, NH * DH / 8}, st[3] = {DM * 2, 128, 8 * DM * 2};
            cuuint32_t box[4] = {64, 8, 2, 8};
            encode(fn, &prm.wo[br], wo, 4, dims, st, box);
        }
    }
    prm.never = 0;
    prm.out = (char*)d_out;
    build_schedule(prm.ops);
    mha2_kernel<<<NCTA, NTHREADS, SMEM_BYTES>>>(prm);
}
```
